```python
import torch

def _softmax(x, axis=-1):
    return torch.softmax(x, dim=axis)

def _gelu(x):
    return torch.nn.functional.gelu(x, approximate='tanh')

def _silu(x):
    return torch.nn.functional.silu(x)

def _sigmoid(x):
    return torch.sigmoid(x)

def _layernorm(x, axis=-1, eps=1e-05):
    m = x.mean(dim=axis, keepdim=True)
    v = x.var(dim=axis, keepdim=True, unbiased=False)
    return (x - m) / torch.sqrt(v + eps)

def _scatter_add(tgt, idx, src, axis=0):
    return tgt.clone().index_add_(axis, idx, src)

def _segment_sum(src, seg, n):
    out = torch.zeros((n,) + src.shape[1:], dtype=src.dtype)
    return out.index_add_(0, seg, src)

def _pad(x, pw):
    flat = tuple((v for pair in reversed(pw) for v in pair))
    return torch.nn.functional.pad(x, flat)
kernel_name = 'recurrent_scan__memory_aug_recurrent_mem_tr__mixer_s_mlp__prompt'

def setup_inputs():

    _w = lambda a: (lambda t: t.to(torch.bfloat16) if t.is_floating_point() else t)(torch.as_tensor(a))

    def _A_setup():
        B, S, Dm = (1, 2048, 448)
        H, Dh = (16, 256)
        M, seg = (8, 32)
        seg = min(seg, S)
        S = S // seg * seg
        return {'x': _w((lambda *s: torch.randn(*s, dtype=torch.bfloat16) * 0.05)(B, S, Dm)), 'mem0': _w((lambda *s: torch.randn(*s, dtype=torch.bfloat16) * 0.2)(B, M, Dm)), 'Wq': _w((lambda *s: torch.randn(*s, dtype=torch.bfloat16) * 1.6)(Dm, H, Dh) * Dm ** (-0.5)), 'Wk': _w((lambda *s: torch.randn(*s, dtype=torch.bfloat16) * 1.6)(Dm, H, Dh) * Dm ** (-0.5)), 'Wv': _w((lambda *s: torch.randn(*s, dtype=torch.bfloat16) * 0.2)(Dm, H, Dh) * Dm ** (-0.5)), 'Wo': _w((lambda *s: torch.randn(*s, dtype=torch.bfloat16) * 0.2)(H, Dh, Dm) * (H * Dh) ** (-0.5)), 'seg_len': seg}
    _A_in = _A_setup()

    def _B_setup():
        B, S, D, F = (1, 2048, 448, 1792)
        return {'x': _w((lambda *s: torch.randn(*s, dtype=torch.bfloat16) * 0.05)(B, S, D)), 'w1': _w((lambda *s: torch.randn(*s, dtype=torch.bfloat16) * 3.2)(D, D) * D ** (-0.5)), 'w2': _w((lambda *s: torch.randn(*s, dtype=torch.bfloat16) * 3.2)(D, D) * D ** (-0.5)), 'w3': _w((lambda *s: torch.randn(*s, dtype=torch.bfloat16) * 3.2)(D, F) * D ** (-0.5)), 'w4': _w((lambda *s: torch.randn(*s, dtype=torch.bfloat16) * 3.2)(F, D) * F ** (-0.5))}
    _B_in = _B_setup()
    return {'A_x': _A_in['x'], 'A_mem0': _A_in['mem0'], 'A_Wq': _A_in['Wq'], 'A_Wk': _A_in['Wk'], 'A_Wv': _A_in['Wv'], 'A_Wo': _A_in['Wo'], 'A_seg_len': _A_in['seg_len'], 'B_x': _B_in['x'], 'B_w1': _B_in['w1'], 'B_w2': _B_in['w2'], 'B_w3': _B_in['w3'], 'B_w4': _B_in['w4']}

def reference(A_x, A_mem0, A_Wq, A_Wk, A_Wv, A_Wo, A_seg_len, B_x, B_w1, B_w2, B_w3, B_w4):

    def _A_ref(x, mem0, Wq, Wk, Wv, Wo, seg_len):
        B, S, Dm = x.shape
        H, Dh = (Wq.shape[1], Wq.shape[2])
        M = mem0.shape[1]
        scale = Dh ** (-0.5)
        n_seg = S // seg_len
        L = M + seg_len
        idx = torch.arange(L)
        mask = (idx[:, None] < M) | (idx[:, None] >= idx[None, :])
        mem = mem0
        outs = []
        for s in range(n_seg):
            xs = x[:, s * seg_len:(s + 1) * seg_len, :].clone()
            h = torch.concatenate([mem, xs], axis=1)
            q = torch.einsum('btd,dhe->bhte', h, Wq)
            k = torch.einsum('btd,dhe->bhte', h, Wk)
            v = torch.einsum('btd,dhe->bhte', h, Wv)
            scores = torch.einsum('bhqe,bhke->bhqk', q, k) * scale
            scores = torch.where(mask[None, None], scores, -1000000000.0)
            p = _softmax(scores, axis=-1)
            o = torch.einsum('bhqk,bhke->bhqe', p, v)
            o = torch.einsum('bhte,hed->btd', o, Wo)
            mem = o[:, :M, :].clone()
            outs.append(o[:, M:, :])
        return torch.concatenate(outs, axis=1)

    def _B_ref(x, w1, w2, w3, w4):
        B, S, D = x.shape
        h = _gelu(_layernorm(x, axis=-1) @ w1)
        c = D // 4
        g0 = _pad(h[:, :, 0 * c:1 * c], ((0, 0), (1, 0), (0, 0)))[:, :S, :]
        g1 = _pad(h[:, :, 1 * c:2 * c], ((0, 0), (0, 1), (0, 0)))[:, 1:, :]
        g2 = _pad(h[:, :, 2 * c:3 * c], ((0, 0), (2, 0), (0, 0)))[:, :S, :]
        g3 = _pad(h[:, :, 3 * c:], ((0, 0), (0, 2), (0, 0)))[:, 2:, :]
        hs = torch.concatenate([g0, g1, g2, g3], axis=-1) @ w2
        x1 = x + hs
        h2 = _gelu(_layernorm(x1, axis=-1) @ w3) @ w4
        return x1 + h2
    x = A_x
    xn = _layernorm(x, axis=-1)
    s = _A_ref(xn, A_mem0, A_Wq, A_Wk, A_Wv, A_Wo, A_seg_len)
    g = _silu(_B_ref(xn, B_w1, B_w2, B_w3, B_w4))
    return x + s * g
```

```cpp
#include <cuda_runtime.h>
#include <cuda_bf16.h>
#include <cuda.h>
#include <stdint.h>

typedef __nv_bfloat16 bf16;

constexpr int S_ = 2048, D_ = 448, NH = 16, NSEG = 64, F_ = 1792;
constexpr int NCL = 7, CSZ = 16, NCHAIN = NCL * CSZ;
constexpr int NMLP = 20, MT = 104;
constexpr float LOG2E = 1.4426950408889634f;

__device__ __align__(1024) bf16 g_xn[S_ * D_];
__device__ __align__(1024) bf16 g_xn2[S_ * D_];
__device__ __align__(1024) uint2 g_sw[S_ * D_ / 2];
__device__ __align__(1024) bf16 g_x1[NMLP * MT * D_];
__device__ __align__(1024) bf16 g_h3[NMLP * MT * F_];
__device__ __align__(1024) unsigned char g_comm[4 << 20];
__device__ __align__(1024) unsigned char g_sx[4 * 16 * 4 * 4480];
__device__ unsigned g_start_cnt;
__device__ unsigned g_epoch;
__device__ unsigned g_done;

__device__ __forceinline__ uint32_t clk() { uint64_t n; asm volatile("mov.u64 %0, %%clock64;" : "=l"(n)); return (uint32_t)n; }
__device__ __forceinline__ bool expired(uint32_t dl) { return (int)(clk() - dl) > 0; }
constexpr uint32_t DEADLINE = 400000000u;
__device__ __forceinline__ uint32_t smem_u32(const void* p) { return (uint32_t)__cvta_generic_to_shared(p); }
__device__ __forceinline__ uint32_t mapa(uint32_t a, uint32_t r) { uint32_t o; asm("mapa.shared::cluster.u32 %0, %1, %2;" : "=r"(o) : "r"(a), "r"(r)); return o; }
__device__ __forceinline__ void mbar_init(uint32_t b, uint32_t c) { asm volatile("mbarrier.init.shared::cta.b64 [%0], %1;" :: "r"(b), "r"(c) : "memory"); }
__device__ __forceinline__ void mbar_arrive(uint32_t b) { asm volatile("mbarrier.arrive.shared::cta.b64 _, [%0];" :: "r"(b) : "memory"); }
__device__ __forceinline__ void mbar_expect(uint32_t b, uint32_t tx) { asm volatile("mbarrier.arrive.expect_tx.shared::cta.b64 _, [%0], %1;" :: "r"(b), "r"(tx) : "memory"); }
__device__ __forceinline__ bool mbar_try(uint32_t b, uint32_t ph) {
    uint32_t p;
    asm volatile("{.reg .pred p; mbarrier.try_wait.parity.shared::cta.b64 p, [%1], %2; selp.u32 %0, 1, 0, p;}" : "=r"(p) : "r"(b), "r"(ph) : "memory");
    return p != 0;
}
__device__ __forceinline__ void mbar_wait(uint32_t b, uint32_t ph, uint32_t dl) {
    if (mbar_try(b, ph)) return;
    while (!mbar_try(b, ph)) { if (expired(dl)) break; }
}
__device__ __forceinline__ void mbar_arrive_if(bool p, uint32_t b) {
    asm volatile("{.reg .pred p; setp.ne.b32 p, %1, 0; @p mbarrier.arrive.shared::cta.b64 _, [%0];}" :: "r"(b), "r"((int)p) : "memory");
}
__device__ __forceinline__ void mbar_expect_if(bool p, uint32_t b, uint32_t tx) {
    asm volatile("{.reg .pred p; setp.ne.b32 p, %2, 0; @p mbarrier.arrive.expect_tx.shared::cta.b64 _, [%0], %1;}" :: "r"(b), "r"(tx), "r"((int)p) : "memory");
}
__device__ __forceinline__ void bar_sync(int id, int n) { asm volatile("bar.sync %0, %1;" :: "r"(id), "r"(n) : "memory"); }
__device__ __forceinline__ void cluster_sync_relaxed() { asm volatile("barrier.cluster.arrive.relaxed.aligned;\nbarrier.cluster.wait.aligned;" ::: "memory"); }
__device__ __forceinline__ void fence_async_smem() { asm volatile("fence.proxy.async.shared::cta;" ::: "memory"); }
__device__ __forceinline__ void fence_async_all() { asm volatile("fence.proxy.async;" ::: "memory"); }

__device__ __forceinline__ void tma_load(uint32_t dst, const CUtensorMap* m, int x, int y, uint32_t bar) {
    asm volatile("cp.async.bulk.tensor.2d.shared::cluster.global.mbarrier::complete_tx::bytes [%0], [%1, {%3, %4}], [%2];"
        :: "r"(dst), "l"(m), "r"(bar), "r"(x), "r"(y) : "memory");
}
__device__ __forceinline__ void tma_load_once(uint32_t dst, const CUtensorMap* m, int x, int y, uint32_t bar) {
    asm volatile("{.reg .b64 pol; createpolicy.fractional.L2::evict_first.b64 pol, 1.0;\n"
                 "cp.async.bulk.tensor.2d.shared::cluster.global.mbarrier::complete_tx::bytes.L2::cache_hint [%0], [%1, {%3, %4}], [%2], pol;}"
        :: "r"(dst), "l"(m), "r"(bar), "r"(x), "r"(y) : "memory");
}
__device__ __forceinline__ void tma_load_mc(uint32_t dst, const CUtensorMap* m, int x, int y, uint32_t bar, uint16_t mask) {
    asm volatile("cp.async.bulk.tensor.2d.shared::cluster.global.mbarrier::complete_tx::bytes.multicast::cluster [%0], [%1, {%3, %4}], [%2], %5;"
        :: "r"(dst), "l"(m), "r"(bar), "r"(x), "r"(y), "h"(mask) : "memory");
}
__device__ __forceinline__ void tma_store(const CUtensorMap* m, int x, int y, uint32_t src) {
    asm volatile("cp.async.bulk.tensor.2d.global.shared::cta.bulk_group [%0, {%1, %2}], [%3];" :: "l"(m), "r"(x), "r"(y), "r"(src) : "memory");
}
__device__ __forceinline__ void bulk_load(uint32_t dst, const void* src, uint32_t bytes, uint32_t bar) {
    asm volatile("cp.async.bulk.shared::cluster.global.mbarrier::complete_tx::bytes [%0], [%1], %2, [%3];" :: "r"(dst), "l"(src), "r"(bytes), "r"(bar) : "memory");
}
__device__ __forceinline__ void bulk_s2c(uint32_t dst, uint32_t src, uint32_t bytes, uint32_t bar) {
    asm volatile("cp.async.bulk.shared::cluster.shared::cta.mbarrier::complete_tx::bytes [%0], [%1], %2, [%3];" :: "r"(dst), "r"(src), "r"(bytes), "r"(bar) : "memory");
}
__device__ __forceinline__ uint32_t desc_lo(uint32_t addr) { return ((addr & 0x3FFFF) >> 4) | (1u << 16); }
__device__ __forceinline__ uint64_t desc_at(uint32_t lo, uint32_t byte_off) {
    uint64_t d; asm("mov.b64 %0, {%1, %2};" : "=l"(d) : "r"(lo + (byte_off >> 4)), "r"(0x40000040u)); return d;
}
__device__ __forceinline__ uint64_t desc_plain(uint32_t addr, uint32_t lbo, uint32_t sbo) {
    return (uint64_t)((addr & 0x3FFFF) >> 4) | ((uint64_t)(lbo >> 4) << 16) | ((uint64_t)(sbo >> 4) << 32);
}
__device__ __forceinline__ void wg_fence() { asm volatile("wgmma.fence.sync.aligned;" ::: "memory"); }
__device__ __forceinline__ void wg_commit() { asm volatile("wgmma.commit_group.sync.aligned;" ::: "memory"); }
template<int N> __device__ __forceinline__ void wg_wait() { asm volatile("wgmma.wait_group.sync.aligned %0;" :: "n"(N) : "memory"); }
__device__ __forceinline__ void wg_rs_n32(float (&d)[16], const uint32_t* a, uint64_t db, int sc) {
    asm volatile("{.reg .pred p; setp.ne.b32 p, %21, 0;\n"
        "wgmma.mma_async.sync.aligned.m64n32k16.f32.bf16.bf16 {%0,%1,%2,%3,%4,%5,%6,%7,%8,%9,%10,%11,%12,%13,%14,%15}, {%16,%17,%18,%19}, %20, p, 1, 1, 0;}"
        : "+f"(d[0]), "+f"(d[1]), "+f"(d[2]), "+f"(d[3]), "+f"(d[4]), "+f"(d[5]), "+f"(d[6]), "+f"(d[7]), "+f"(d[8]), "+f"(d[9]), "+f"(d[10]), "+f"(d[11]), "+f"(d[12]), "+f"(d[13]), "+f"(d[14]), "+f"(d[15])
        : "r"(a[0]), "r"(a[1]), "r"(a[2]), "r"(a[3]), "l"(db), "r"(sc));
}
template<int TA, int TB = 0> __device__ __forceinline__ void wg_ss_n112(float (&d)[56], uint64_t da, uint64_t db, int sc) {
    asm volatile("{.reg .pred p; setp.ne.b32 p, %58, 0;\n"
        "wgmma.mma_async.sync.aligned.m64n112k16.f32.bf16.bf16 {%0,%1,%2,%3,%4,%5,%6,%7,%8,%9,%10,%11,%12,%13,%14,%15,%16,%17,%18,%19,%20,%21,%22,%23,%24,%25,%26,%27,%28,%29,%30,%31,%32,%33,%34,%35,%36,%37,%38,%39,%40,%41,%42,%43,%44,%45,%46,%47,%48,%49,%50,%51,%52,%53,%54,%55}, %56, %57, p, 1, 1, %59, %60;}"
        : "+f"(d[0]), "+f"(d[1]), "+f"(d[2]), "+f"(d[3]), "+f"(d[4]), "+f"(d[5]), "+f"(d[6]), "+f"(d[7]), "+f"(d[8]), "+f"(d[9]), "+f"(d[10]), "+f"(d[11]), "+f"(d[12]), "+f"(d[13]), "+f"(d[14]), "+f"(d[15]), "+f"(d[16]), "+f"(d[17]), "+f"(d[18]), "+f"(d[19]), "+f"(d[20]), "+f"(d[21]), "+f"(d[22]), "+f"(d[23]), "+f"(d[24]), "+f"(d[25]), "+f"(d[26]), "+f"(d[27]), "+f"(d[28]), "+f"(d[29]), "+f"(d[30]), "+f"(d[31]), "+f"(d[32]), "+f"(d[33]), "+f"(d[34]), "+f"(d[35]), "+f"(d[36]), "+f"(d[37]), "+f"(d[38]), "+f"(d[39]), "+f"(d[40]), "+f"(d[41]), "+f"(d[42]), "+f"(d[43]), "+f"(d[44]), "+f"(d[45]), "+f"(d[46]), "+f"(d[47]), "+f"(d[48]), "+f"(d[49]), "+f"(d[50]), "+f"(d[51]), "+f"(d[52]), "+f"(d[53]), "+f"(d[54]), "+f"(d[55])
        : "l"(da), "l"(db), "r"(sc), "n"(TA), "n"(TB));
}
template<int TA, int TB = 0> __device__ __forceinline__ void wg_ss_n104(float (&d)[52], uint64_t da, uint64_t db, int sc) {
    asm volatile("{.reg .pred p; setp.ne.b32 p, %54, 0;\n"
        "wgmma.mma_async.sync.aligned.m64n104k16.f32.bf16.bf16 {%0,%1,%2,%3,%4,%5,%6,%7,%8,%9,%10,%11,%12,%13,%14,%15,%16,%17,%18,%19,%20,%21,%22,%23,%24,%25,%26,%27,%28,%29,%30,%31,%32,%33,%34,%35,%36,%37,%38,%39,%40,%41,%42,%43,%44,%45,%46,%47,%48,%49,%50,%51}, %52, %53, p, 1, 1, %55, %56;}"
        : "+f"(d[0]), "+f"(d[1]), "+f"(d[2]), "+f"(d[3]), "+f"(d[4]), "+f"(d[5]), "+f"(d[6]), "+f"(d[7]), "+f"(d[8]), "+f"(d[9]), "+f"(d[10]), "+f"(d[11]), "+f"(d[12]), "+f"(d[13]), "+f"(d[14]), "+f"(d[15]), "+f"(d[16]), "+f"(d[17]), "+f"(d[18]), "+f"(d[19]), "+f"(d[20]), "+f"(d[21]), "+f"(d[22]), "+f"(d[23]), "+f"(d[24]), "+f"(d[25]), "+f"(d[26]), "+f"(d[27]), "+f"(d[28]), "+f"(d[29]), "+f"(d[30]), "+f"(d[31]), "+f"(d[32]), "+f"(d[33]), "+f"(d[34]), "+f"(d[35]), "+f"(d[36]), "+f"(d[37]), "+f"(d[38]), "+f"(d[39]), "+f"(d[40]), "+f"(d[41]), "+f"(d[42]), "+f"(d[43]), "+f"(d[44]), "+f"(d[45]), "+f"(d[46]), "+f"(d[47]), "+f"(d[48]), "+f"(d[49]), "+f"(d[50]), "+f"(d[51])
        : "l"(da), "l"(db), "r"(sc), "n"(TA), "n"(TB));
}
template<int TA, int TB = 0> __device__ __forceinline__ void wg_ss_n40(float (&d)[20], uint64_t da, uint64_t db, int sc) {
    asm volatile("{.reg .pred p; setp.ne.b32 p, %22, 0;\n"
        "wgmma.mma_async.sync.aligned.m64n40k16.f32.bf16.bf16 {%0,%1,%2,%3,%4,%5,%6,%7,%8,%9,%10,%11,%12,%13,%14,%15,%16,%17,%18,%19}, %20, %21, p, 1, 1, %23, %24;}"
        : "+f"(d[0]), "+f"(d[1]), "+f"(d[2]), "+f"(d[3]), "+f"(d[4]), "+f"(d[5]), "+f"(d[6]), "+f"(d[7]), "+f"(d[8]), "+f"(d[9]), "+f"(d[10]), "+f"(d[11]), "+f"(d[12]), "+f"(d[13]), "+f"(d[14]), "+f"(d[15]), "+f"(d[16]), "+f"(d[17]), "+f"(d[18]), "+f"(d[19])
        : "l"(da), "l"(db), "r"(sc), "n"(TA), "n"(TB));
}
template<int TA, int TB = 0> __device__ __forceinline__ void wg_ss_n32(float (&d)[16], uint64_t da, uint64_t db, int sc) {
    asm volatile("{.reg .pred p; setp.ne.b32 p, %18, 0;\n"
        "wgmma.mma_async.sync.aligned.m64n32k16.f32.bf16.bf16 {%0,%1,%2,%3,%4,%5,%6,%7,%8,%9,%10,%11,%12,%13,%14,%15}, %16, %17, p, 1, 1, %19, %20;}"
        : "+f"(d[0]), "+f"(d[1]), "+f"(d[2]), "+f"(d[3]), "+f"(d[4]), "+f"(d[5]), "+f"(d[6]), "+f"(d[7]), "+f"(d[8]), "+f"(d[9]), "+f"(d[10]), "+f"(d[11]), "+f"(d[12]), "+f"(d[13]), "+f"(d[14]), "+f"(d[15])
        : "l"(da), "l"(db), "r"(sc), "n"(TA), "n"(TB));
}
__device__ __forceinline__ void mma16816(float (&d)[4], uint32_t a0, uint32_t a1, uint32_t a2, uint32_t a3, uint32_t b0, uint32_t b1) {
    asm("mma.sync.aligned.m16n8k16.row.col.f32.bf16.bf16.f32 {%0,%1,%2,%3}, {%4,%5,%6,%7}, {%8,%9}, {%0,%1,%2,%3};"
        : "+f"(d[0]), "+f"(d[1]), "+f"(d[2]), "+f"(d[3]) : "r"(a0), "r"(a1), "r"(a2), "r"(a3), "r"(b0), "r"(b1));
}
__device__ __forceinline__ void mma1688(float (&d)[4], uint32_t a0, uint32_t a1, uint32_t b0) {
    asm("mma.sync.aligned.m16n8k8.row.col.f32.bf16.bf16.f32 {%0,%1,%2,%3}, {%4,%5}, {%6}, {%0,%1,%2,%3};"
        : "+f"(d[0]), "+f"(d[1]), "+f"(d[2]), "+f"(d[3]) : "r"(a0), "r"(a1), "r"(b0));
}
__device__ __forceinline__ void mma16816v(float (&d)[4], uint32_t a0, uint32_t a1, uint32_t a2, uint32_t a3, uint32_t b0, uint32_t b1) {
    asm volatile("mma.sync.aligned.m16n8k16.row.col.f32.bf16.bf16.f32 {%0,%1,%2,%3}, {%4,%5,%6,%7}, {%8,%9}, {%0,%1,%2,%3};"
        : "+f"(d[0]), "+f"(d[1]), "+f"(d[2]), "+f"(d[3]) : "r"(a0), "r"(a1), "r"(a2), "r"(a3), "r"(b0), "r"(b1));
}
__device__ __forceinline__ void mma1688v(float (&d)[4], uint32_t a0, uint32_t a1, uint32_t b0) {
    asm volatile("mma.sync.aligned.m16n8k8.row.col.f32.bf16.bf16.f32 {%0,%1,%2,%3}, {%4,%5}, {%6}, {%0,%1,%2,%3};"
        : "+f"(d[0]), "+f"(d[1]), "+f"(d[2]), "+f"(d[3]) : "r"(a0), "r"(a1), "r"(b0));
}
__device__ __forceinline__ void ldsm4(uint32_t* r, uint32_t a) {
    asm volatile("ldmatrix.sync.aligned.m8n8.x4.shared.b16 {%0,%1,%2,%3}, [%4];" : "=r"(r[0]), "=r"(r[1]), "=r"(r[2]), "=r"(r[3]) : "r"(a) : "memory");
}
__device__ __forceinline__ void ldsm4t(uint32_t* r, uint32_t a) {
    asm volatile("ldmatrix.sync.aligned.m8n8.x4.trans.shared.b16 {%0,%1,%2,%3}, [%4];" : "=r"(r[0]), "=r"(r[1]), "=r"(r[2]), "=r"(r[3]) : "r"(a) : "memory");
}
__device__ __forceinline__ void stsm4(uint32_t a, uint32_t r0, uint32_t r1, uint32_t r2, uint32_t r3) {
    asm volatile("stmatrix.sync.aligned.m8n8.x4.shared.b16 [%0], {%1,%2,%3,%4};" :: "r"(a), "r"(r0), "r"(r1), "r"(r2), "r"(r3) : "memory");
}
__device__ __forceinline__ void stsm4t(uint32_t a, uint32_t r0, uint32_t r1, uint32_t r2, uint32_t r3) {
    asm volatile("stmatrix.sync.aligned.m8n8.x4.trans.shared.b16 [%0], {%1,%2,%3,%4};" :: "r"(a), "r"(r0), "r"(r1), "r"(r2), "r"(r3) : "memory");
}
__device__ __forceinline__ void stsm2t(uint32_t a, uint32_t r0, uint32_t r1) {
    asm volatile("stmatrix.sync.aligned.m8n8.x2.trans.shared.b16 [%0], {%1,%2};" :: "r"(a), "r"(r0), "r"(r1) : "memory");
}
__device__ __forceinline__ void sts32(uint32_t a, uint32_t v) { asm volatile("st.shared.b32 [%0], %1;" :: "r"(a), "r"(v) : "memory"); }
__device__ __forceinline__ void sts64(uint32_t a, uint32_t x, uint32_t y) { asm volatile("st.shared.v2.b32 [%0], {%1,%2};" :: "r"(a), "r"(x), "r"(y) : "memory"); }
__device__ __forceinline__ void sts128(uint32_t a, uint4 v) { asm volatile("st.shared.v4.b32 [%0], {%1,%2,%3,%4};" :: "r"(a), "r"(v.x), "r"(v.y), "r"(v.z), "r"(v.w) : "memory"); }
__device__ __forceinline__ uint32_t lds32(uint32_t a) { uint32_t v; asm volatile("ld.shared.b32 %0, [%1];" : "=r"(v) : "r"(a) : "memory"); return v; }
__device__ __forceinline__ uint2 lds64(uint32_t a) { uint2 v; asm volatile("ld.shared.v2.b32 {%0,%1}, [%2];" : "=r"(v.x), "=r"(v.y) : "r"(a) : "memory"); return v; }
__device__ __forceinline__ void st_async32(uint32_t a, uint32_t bar, uint32_t v) {
    asm volatile("st.async.weak.shared::cluster.mbarrier::complete_tx::bytes.b32 [%0], %2, [%1];" :: "r"(a), "r"(bar), "r"(v) : "memory");
}
__device__ __forceinline__ void st_async64(uint32_t a, uint32_t bar, uint32_t x, uint32_t y) {
    asm volatile("st.async.weak.shared::cluster.mbarrier::complete_tx::bytes.v2.b32 [%0], {%2,%3}, [%1];" :: "r"(a), "r"(bar), "r"(x), "r"(y) : "memory");
}
__device__ __forceinline__ uint32_t ldg_rlx32(const void* p) { uint32_t v; asm volatile("ld.relaxed.gpu.global.b32 %0, [%1];" : "=r"(v) : "l"(p) : "memory"); return v; }
__device__ __forceinline__ uint4 ldg_rlx128(const void* p) {
    uint4 v; asm volatile("ld.relaxed.gpu.global.v4.b32 {%0,%1,%2,%3}, [%4];" : "=r"(v.x), "=r"(v.y), "=r"(v.z), "=r"(v.w) : "l"(p) : "memory"); return v;
}
__device__ __forceinline__ void ldg_rlx32_if(uint32_t& v, uint32_t c, const void* p) {
    asm volatile("{.reg .pred p; setp.ne.b32 p, %2, 0; @p ld.relaxed.gpu.global.b32 %0, [%1];}" : "+r"(v) : "l"(p), "r"(c) : "memory");
}
__device__ __forceinline__ uint2 ldg_rlx64(const void* p) { uint2 v; asm volatile("ld.relaxed.gpu.global.v2.b32 {%0,%1}, [%2];" : "=r"(v.x), "=r"(v.y) : "l"(p) : "memory"); return v; }
__device__ __forceinline__ void stg_rlx32(void* p, uint32_t v) { asm volatile("st.relaxed.gpu.global.b32 [%0], %1;" :: "l"(p), "r"(v) : "memory"); }
__device__ __forceinline__ void stg_rlx32_if(bool p, void* a, uint32_t v) {
    asm volatile("{.reg .pred p; setp.ne.b32 p, %2, 0; @p st.relaxed.gpu.global.b32 [%0], %1;}" :: "l"(a), "r"(v), "r"((int)p) : "memory");
}
template<int LUT> __device__ __forceinline__ uint32_t lop3(uint32_t a, uint32_t b, uint32_t c) {
    uint32_t r; asm("lop3.b32 %0, %1, %2, %3, %4;" : "=r"(r) : "r"(a), "r"(b), "r"(c), "n"(LUT)); return r;
}
__device__ __forceinline__ uint32_t ldg_acq32(const void* p) { uint32_t v; asm volatile("ld.acquire.gpu.global.b32 %0, [%1];" : "=r"(v) : "l"(p) : "memory"); return v; }

__device__ __forceinline__ uint32_t pack_bf(float lo, float hi) { uint32_t r; asm("cvt.rn.bf16x2.f32 %0, %1, %2;" : "=r"(r) : "f"(hi), "f"(lo)); return r; }
__device__ __forceinline__ float bf_lo(uint32_t w) { return __uint_as_float(w << 16); }
__device__ __forceinline__ float bf_hi(uint32_t w) { return __uint_as_float(w & 0xffff0000u); }
__device__ __forceinline__ float rbf(float v) { return __bfloat162float(__float2bfloat16_rn(v)); }
__device__ __forceinline__ float ex2(float v) { float r; asm("ex2.approx.ftz.f32 %0, %1;" : "=f"(r) : "f"(v)); return r; }
__device__ __forceinline__ float rcp(float v) { float r; asm("rcp.approx.ftz.f32 %0, %1;" : "=f"(r) : "f"(v)); return r; }
__device__ __forceinline__ float shx(float v, int m) { return __shfl_xor_sync(0xffffffffu, v, m); }
__device__ __forceinline__ float gelu_tanh(float u) {
    const float a = u * fmaf(u * u, 0.7978845608028654f * 0.044715f, 0.7978845608028654f), hf = 0.5f * u;
    float t;
    asm("tanh.approx.f32 %0, %1;" : "=f"(t) : "f"(a));
    return fmaf(hf, t, hf);
}
template<int R> __device__ __forceinline__ void ln_rows(uint32_t (&w)[R][7]) {
    float mean[R], sq[R];
#pragma unroll
    for (int r = 0; r < R; r++) {
        mean[r] = 0.f;
#pragma unroll
        for (int i = 0; i < 7; i++) mean[r] += bf_lo(w[r][i]) + bf_hi(w[r][i]);
    }
#pragma unroll
    for (int m = 16; m >= 1; m >>= 1)
#pragma unroll
        for (int r = 0; r < R; r++) mean[r] += shx(mean[r], m);
#pragma unroll
    for (int r = 0; r < R; r++) {
        mean[r] *= 1.0f / D_; sq[r] = 0.f;
#pragma unroll
        for (int i = 0; i < 7; i++) { const float a = bf_lo(w[r][i]) - mean[r], b = bf_hi(w[r][i]) - mean[r]; sq[r] = fmaf(a, a, fmaf(b, b, sq[r])); }
    }
#pragma unroll
    for (int m = 16; m >= 1; m >>= 1)
#pragma unroll
        for (int r = 0; r < R; r++) sq[r] += shx(sq[r], m);
#pragma unroll
    for (int r = 0; r < R; r++) {
        const uint32_t mb2 = pack_bf(mean[r], mean[r]);
        const float den = __frcp_rn(rbf(sqrtf(rbf(rbf(sq[r] * (1.0f / D_)) + 1e-5f))));
#pragma unroll
        for (int i = 0; i < 7; i++) {
            uint32_t d;
            asm("sub.rn.bf16x2 %0, %1, %2;" : "=r"(d) : "r"(w[r][i]), "r"(mb2));
            w[r][i] = pack_bf(bf_lo(d) * den, bf_hi(d) * den);
        }
    }
}
__device__ __forceinline__ void ln_row(uint32_t (&w)[7]) { ln_rows<1>(reinterpret_cast<uint32_t (&)[1][7]>(w)); }

constexpr int XT_BYTES = 28672;
constexpr int ST_BYTES = 14336;
constexpr int OFF_XT = 0;
constexpr int OFF_SX = 4 * XT_BYTES, SX_BYTES = 4480, OFF_P = OFF_SX + 4608, OFF_EX = OFF_P + 3072, OFF_OS = OFF_EX + 2048;
static_assert(OFF_OS + 4 * 4352 <= 5 * XT_BYTES, "slot 4 overflow");
constexpr int OFF_MT = 5 * XT_BYTES;
constexpr int OFF_U = OFF_MT + 16384;
constexpr int OFF_WQ = OFF_U, OFF_WO = OFF_U + 32768;
constexpr int U_K = 0, KP = 640, U_V = 5120, VP = 768, U_RSX = 11264, U_RS = 15360;
constexpr int OFF_BAR = OFF_U + 65536;
constexpr int CH_SMEM = OFF_BAR + 1024 + 1024;
constexpr int CH_THREADS = 512;
enum { B_VB = 0, B_KQ = 8, B_EX = 24, B_VA = 16, B_PV = 32, B_X = 40, B_KF = 48, B_RS = 56, B_RSX = 64, B_PUB = 72, B_SX = 80, B_XD = 88, B_P = 96, B_TPUB = 104 };
enum { P_STE = 512, P_STF = 576, P_VOTE = 656, P_SIDE = 672, P_VAL = 704 };
constexpr uint32_t D_M = 375, D_SMX = 330, D_SMM = 595;
constexpr int TGA0 = 13;
enum { ID_M = 0, ID_SMM = 8, ID_SMX = 24, ID_P = 40, ID_PROBE = 56 };
__device__ __forceinline__ unsigned char* cblk(unsigned char* comm, int id, int cls) {
    const int off = (id >> 1) * 65536 + (id & 1) * 8192;
    return comm + off + (((__popc((off >> 12) & 0xB3) ^ cls) & 1) << 12);
}
__device__ __forceinline__ uint32_t put_tag(uint32_t w, uint32_t tag) { return lop3<0xEA>(w, ~1u, tag); }
__device__ __forceinline__ uint32_t bad2(uint32_t a, uint32_t b, uint32_t T) { return lop3<0x7E>(a, b, T); }
__device__ __forceinline__ uint32_t or3(uint32_t a, uint32_t b, uint32_t c) { return lop3<0xFE>(a, b, c); }
__device__ __forceinline__ uint32_t bad4(const uint4& v, uint32_t T) { return bad2(v.x, v.y, T) | bad2(v.z, v.w, T); }
__device__ __forceinline__ void spin_until(uint32_t t) { while (t - clk() - 1u < 4096u) {} }
__device__ __forceinline__ void spin(uint32_t n) { const uint32_t t0 = clk(); while (clk() - t0 < n) {} }
__device__ __forceinline__ uint32_t atom_add(unsigned* p) { uint32_t o; asm volatile("atom.relaxed.gpu.global.add.u32 %0, [%1], 1;" : "=r"(o) : "l"(p) : "memory"); return o; }
__device__ __forceinline__ uint32_t opaque(uint32_t v, int lane) { return __shfl_sync(0xffffffffu, v, lane); }
__device__ __forceinline__ float fsel(bool p, float a, float b) { float r; asm("{.reg .pred p; setp.ne.b32 p, %3, 0; selp.f32 %0, %1, %2, p;}" : "=f"(r) : "f"(a), "f"(b), "r"((int)p)); return r; }
constexpr float SAFE = 30.0f;
struct Cur {
    uint32_t o, b, ph;
    __device__ __forceinline__ Cur next(uint32_t bars) const { Cur c; c.o = (o + 16384u) & 0xFFFFu; c.b = bars + (c.o >> 7); c.ph = ph ^ (c.o == 0 ? 1u : 0u); return c; }
};
#define BAD7(r, T) or3(bad2(r[0], r[1], T), bad2(r[2], r[3], T), lop3<0xF6>(bad2(r[4], r[5], T), r[6], T))
#define SUM7_LO(r) (((bf_lo(r[0]) + bf_lo(r[1])) + (bf_lo(r[2]) + bf_lo(r[3]))) + ((bf_lo(r[4]) + bf_lo(r[5])) + bf_lo(r[6])))
#define SUM7_HI(r) (((bf_hi(r[0]) + bf_hi(r[1])) + (bf_hi(r[2]) + bf_hi(r[3]))) + ((bf_hi(r[4]) + bf_hi(r[5])) + bf_hi(r[6])))
#define ZERO4(d) do { d[0] = d[1] = d[2] = d[3] = 0.f; } while (0)

template<int K0, int K1>
__device__ __forceinline__ void token_gemm(float (&acc)[16], const uint32_t (&w)[112], uint32_t xt) {
    const uint32_t lo = desc_lo(xt);
    wg_fence();
#pragma unroll
    for (int ks = K0; ks < K1; ks++) wg_rs_n32(acc, &w[4 * ks], desc_at(lo, (ks >> 2) * 4096 + (ks & 3) * 32), ks > 0);
    wg_commit();
    wg_wait<0>();
}
__device__ __forceinline__ void mem_gemm(float (&o)[4], const uint32_t (&w)[112], uint32_t mtl) {
    float d[4][4];
    uint32_t b[14][4];
#pragma unroll
    for (int i = 0; i < 4; i++) ZERO4(d[i]);
#pragma unroll
    for (int p = 0; p < 7; p++) ldsm4t(b[p], mtl + 512 * p);
#pragma unroll
    for (int p = 0; p < 14; p++) {
        if (p < 7) ldsm4t(b[p + 7], mtl + 512 * (p + 7));
        mma16816(d[(2 * p) & 3], w[8 * p], w[8 * p + 1], w[8 * p + 2], w[8 * p + 3], b[p][0], b[p][1]);
        mma16816(d[(2 * p + 1) & 3], w[8 * p + 4], w[8 * p + 5], w[8 * p + 6], w[8 * p + 7], b[p][2], b[p][3]);
    }
#pragma unroll
    for (int i = 0; i < 4; i++) o[i] = (d[0][i] + d[1][i]) + (d[2][i] + d[3][i]);
}
__device__ __forceinline__ uint32_t mem_scores(const uint32_t (&a)[8], const uint32_t (&kb)[8]) {
    float c0[4] = {0.f, 0.f, 0.f, 0.f}, c1[4] = {0.f, 0.f, 0.f, 0.f};
    mma16816(c0, a[0], 0u, a[1], 0u, kb[0], kb[1]);
    mma16816(c1, a[2], 0u, a[3], 0u, kb[2], kb[3]);
    mma16816(c0, a[4], 0u, a[5], 0u, kb[4], kb[5]);
    mma16816(c1, a[6], 0u, a[7], 0u, kb[6], kb[7]);
    return pack_bf(c0[0] + c1[0], c0[1] + c1[1]);
}
template<int G, typename F>
__device__ __forceinline__ void prologue_weights(uint32_t (&w)[112], uint32_t sb, int lane, uint32_t dl, F&& after_first) {
    const uint32_t bars = sb + OFF_BAR;
#pragma unroll
    for (int nh = 0; nh < 4; nh++) {
        float acc[56];
#pragma unroll 1
        for (int kb = 0; kb < 4; kb++) {
            const int slot = 2 * kb + G;
            const uint32_t alo = desc_lo(G == 0 ? sb + OFF_WQ + kb * 8192 : sb + OFF_WO + kb * 8192);
            const uint32_t blo = desc_lo(sb + OFF_XT + XT_BYTES + slot * ST_BYTES);
            mbar_wait(bars + P_STF + slot * 8, nh & 1, dl);
            wg_fence();
#pragma unroll
            for (int ks = 0; ks < 4; ks++) wg_ss_n112<G>(acc, desc_at(alo, G == 0 ? ks * 32 : ks * 2048), desc_at(blo, ks * 32), (kb | ks) != 0);
            wg_commit();
            wg_wait<0>();
            mbar_arrive_if(lane == 0, bars + P_STE + slot * 8);
        }
        if (nh == 0) after_first();
        const float sc = G == 0 ? 0.0625f : 1.0f;
#pragma unroll
        for (int u = 0; u < 28; u++) w[nh * 28 + u] = pack_bf(acc[2 * u] * sc, acc[2 * u + 1] * sc);
    }
}

__global__ void __launch_bounds__(CH_THREADS, 1)
chain_kernel(const __grid_constant__ CUtensorMap mWq, const __grid_constant__ CUtensorMap mWk, const __grid_constant__ CUtensorMap mWv,
             const __grid_constant__ CUtensorMap mWo, const __grid_constant__ CUtensorMap mXn,
             const bf16* __restrict__ x, const bf16* __restrict__ mem0, unsigned char* __restrict__ comm) {
    extern __shared__ unsigned char smem_raw[];
    const uint32_t sb = (smem_u32(smem_raw) + 1023u) & ~1023u;
    const uint32_t bars = sb + OFF_BAR;
    const uint32_t dl = clk() + DEADLINE;
    uint32_t h, j;
    asm("mov.u32 %0, %%cluster_ctarank;" : "=r"(h));
    asm("mov.u32 %0, %%clusterid.x;" : "=r"(j));
    const int tid = threadIdx.x;
    const int lane = __shfl_sync(0xffffffffu, tid & 31, tid & 31);
    const int wg = __shfl_sync(0xffffffffu, tid >> 7, 0), w = __shfl_sync(0xffffffffu, (tid >> 5) & 3, 0);
    const int g = lane >> 2, t = lane & 3, cta = j * CSZ + h;
    asm volatile("griddepcontrol.launch_dependents;" ::: "memory");
    const int r0 = cta + NCHAIN * ((tid >> 5) & 7);
    uint32_t xr[3][7], mq[2][4], mr[2][4];
    if (wg >= 2 && tid < 480) {
#pragma unroll
        for (int q = 0; q < 3; q++) {
            const uint32_t* px = reinterpret_cast<const uint32_t*>(x + min(r0 + NCHAIN * 7 * q, S_ - 1) * D_) + lane;
#pragma unroll
            for (int i = 0; i < 7; i++) xr[q][i] = __ldg(px + 32 * i);
        }
    }
    if (wg < 2) {
        const unsigned char* m0 = reinterpret_cast<const unsigned char*>(mem0);
#pragma unroll
        for (int q = 0; q < 2; q++)
#pragma unroll
            for (int r = 0; r < 4; r++) {
                const int c = min(tid + 256 * q, D_ - 1) * 2;
                mq[q][r] = *reinterpret_cast<const uint16_t*>(m0 + 2 * r * D_ * 2 + c);
                mr[q][r] = *reinterpret_cast<const uint16_t*>(m0 + (2 * r + 1) * D_ * 2 + c);
            }
    }
    if (wg == 3) {
        if (lane == 0) {
            if (w < 2) {
#pragma unroll 1
                for (int i = 0; i < 4; i++) {
                    const uint32_t bar = bars + P_STF + (2 * i + w) * 8;
                    mbar_init(bar, 1);
                    fence_async_smem();
                    mbar_expect(bar, ST_BYTES + 8192);
                    tma_load_once(sb + OFF_WQ + w * 32768 + i * 8192, w ? &mWo : &mWq, w ? 64 * j : h * 256 + i * 64, w ? h * 256 + i * 64 : 64 * j, bar);
                    tma_load_once(sb + OFF_XT + XT_BYTES + (2 * i + w) * ST_BYTES, w ? &mWv : &mWk, h * 256 + i * 64, 0, bar);
                }
            } else if (w == 2) {
                asm volatile("prefetch.tensormap [%0];" :: "l"(&mXn) : "memory");
            }
        }
        __syncwarp();
    }
    auto init_share = [&]() {
        if (lane == 0) {
        const int k = (tid >> 5) * 8 + 8;
#pragma unroll 1
        for (int i = 0; i < 4; i++) {
            const uint32_t bar = bars + i * 128 + k;
            if (k == B_P) mbar_init(bars + i * 128 + B_VB, 4);
            mbar_init(bar, k == B_PV ? 12 : (k == B_KQ || k == B_EX || k == B_XD || k == B_VA) ? 4 : k == B_RSX ? 2 : 1);
            if (k == B_RS) mbar_expect(bar, 1024);
            if (k == B_RSX) { mbar_expect(bar, 2048); mbar_expect(bar, 2048); }
        }
        if (tid < 256) mbar_init(bars + P_STE + (tid >> 5) * 8, 4);
        if (tid == 256) { mbar_init(bars + P_VOTE, 1); mbar_expect(bars + P_VOTE, 64); }
        asm volatile("fence.mbarrier_init.release.cluster;" ::: "memory");
    }
        __syncwarp();
        asm volatile("barrier.cluster.arrive.relaxed.aligned;" ::: "memory");
    };
    auto mem_share = [&]() {
        init_share();
        bar_sync(5, 384);
    };
    auto mem_store = [&]() {
        sts128(sb + OFF_MT + tid * 16, make_uint4(mq[0][0] | (mr[0][0] << 16), mq[0][1] | (mr[0][1] << 16), mq[0][2] | (mr[0][2] << 16), mq[0][3] | (mr[0][3] << 16)));
        if (tid < D_ - 256) sts128(sb + OFF_MT + (tid + 256) * 16, make_uint4(mq[1][0] | (mr[1][0] << 16), mq[1][1] | (mr[1][1] << 16), mq[1][2] | (mr[1][2] << 16), mq[1][3] | (mr[1][3] << 16)));
    };
    auto ln_share = [&]() {
#pragma unroll 1
        for (int q = 0; q < 6; q++) {
            const int r = r0 + NCHAIN * 7 * (q >> 1);
            if (r >= S_) break;
            ln_row(xr[0]);
            uint32_t* pn = reinterpret_cast<uint32_t*>(((q & 1) ? g_xn2 : g_xn) + r * D_) + lane;
#pragma unroll
            for (int i = 0; i < 7; i++) {
                pn[32 * i] = xr[0][i];
                if (q & 1) { xr[0][i] = xr[1][i]; xr[1][i] = xr[2][i]; }
            }
        }
        if (tid < 288) bar_sync(2, 224); else asm volatile("bar.arrive 2, 224;" ::: "memory");
    };
    const uint32_t ub = sb + OFF_U;
    const uint32_t msum = 2 * (sb + OFF_MT + lane * 16) + 8192;
    Cur c0;
    c0.o = 49152u; c0.b = bars + 384; c0.ph = 1u;

    if (wg == 0) {
        mem_share();
        asm volatile("setmaxnreg.inc.sync.aligned.u32 184;");
        uint32_t wt[112];
        prologue_weights<0>(wt, sb, lane, dl, mem_store);
        asm volatile("barrier.cluster.wait.aligned;" ::: "memory");
        bar_sync(6, 256);
        asm volatile("barrier.cluster.arrive.relaxed.aligned;" ::: "memory");
        const uint32_t st_off = ub + U_K + (2 * w + ((lane >> 3) & 1)) * KP + (lane >> 4) * 128 + (lane & 7) * 16;
        const uint32_t ks_off = opaque(ub + U_K + 2 * w * KP + 512 + lane * 4, lane), kl_off = opaque(ub + U_K + (lane >> 3) * KP + 512 + (lane & 7) * 16, lane);
        const bool kf_src = w == 3 && lane == 0;
        unsigned char* po = cblk(comm, ID_SMM + h, 0) + w * 1024 + j * 128 + lane * 4;
        const int dpo = (int)(cblk(comm, ID_SMM + h, 1) - cblk(comm, ID_SMM + h, 0));
        uint32_t mt = opaque(sb + OFF_MT + lane * 16, lane), mj = 1024 * j;
        {
            float acc[16];
            mbar_wait(bars + B_X, 0, dl);
            token_gemm<0, 28>(acc, wt, sb + OFF_XT);
            stsm4(st_off, pack_bf(acc[0], acc[1]), pack_bf(acc[2], acc[3]), pack_bf(acc[4], acc[5]), pack_bf(acc[6], acc[7]));
            stsm4(st_off + 256, pack_bf(acc[8], acc[9]), pack_bf(acc[10], acc[11]), pack_bf(acc[12], acc[13]), pack_bf(acc[14], acc[15]));
            __syncwarp();
            mbar_arrive_if(lane == 0, bars + B_KQ);
        }
        bar_sync(0, 512);
        asm volatile("barrier.cluster.wait.aligned;" ::: "memory");
        const int side = (int)lds32(bars + P_SIDE);
        const unsigned char* pm0 = cblk(comm, ID_M, side) + (w * 32 + lane) * 16 + 49152;
        const int dm1 = (int)(cblk(comm, ID_M + 1, side) - cblk(comm, ID_M, side));
        Cur p1 = c0, cur = c0.next(bars);
#pragma unroll 1
        for (int s = 0; s < NSEG; s++) {
            const Cur nx = cur.next(bars);
            {
                const uint32_t ks0 = ks_off + cur.o, kl0 = kl_off + cur.o;
                if (s > 0) {
                    const uint32_t T = p1.ph - 1u, md = mt + w * 512;
                    const unsigned char* pm1 = pm0 + dm1;
                    uint4 v0, v1, v2, v3 = make_uint4(T, T, T, T);
                    mbar_wait(p1.b + B_PUB, p1.ph, dl);
                    spin_until(lds32(p1.b + B_TPUB));
                    if (w < 2) v3 = ldg_rlx128(pm1 + 2048);
                    v0 = ldg_rlx128(pm0); v1 = ldg_rlx128(pm0 + 2048); v2 = ldg_rlx128(pm1);
                    if (w < 2) sts128(md + 6144, v3);
                    sts128(md, v0); sts128(md + 2048, v1); sts128(md + 4096, v2);
                    while (__any_sync(0xffffffffu, ((or3(bad4(v3, T), bad4(v0, T), bad4(v1, T)) | bad4(v2, T)) & 1u) != 0)) {
                        if (bad4(v3, T) & 1u) { v3 = ldg_rlx128(pm1 + 2048); sts128(md + 6144, v3); }
                        if (bad4(v0, T) & 1u) { v0 = ldg_rlx128(pm0); sts128(md, v0); }
                        if (bad4(v1, T) & 1u) { v1 = ldg_rlx128(pm0 + 2048); sts128(md + 2048, v1); }
                        if (bad4(v2, T) & 1u) { v2 = ldg_rlx128(pm1); sts128(md + 4096, v2); }
                        __syncwarp();
                        if (expired(dl)) break;
                    }
                }
                bar_sync(4, 256);
                float o[4];
                mem_gemm(o, wt, mt);
                uint32_t ma[8], kb[8];
                ldsm4t(ma, mt + mj);
                ldsm4t(ma + 4, mt + mj + 512);
                sts32(ks0, pack_bf(o[0], o[1]));
                sts32(ks0 + KP, pack_bf(o[2], o[3]));
                bar_sync(1, 128);
                mbar_arrive_if(kf_src, cur.b + B_KF);
                ldsm4t(kb, kl0);
                ldsm4t(kb + 4, kl0 + 4 * KP);
                unsigned char* po2 = po + dpo;
                const uint32_t sw = put_tag(mem_scores(ma, kb), cur.ph ^ 1u);
                stg_rlx32(po, sw);
                stg_rlx32(po2, sw);
                if (s < NSEG - 1) mbar_wait(nx.b + B_X, nx.ph, dl);
                fence_async_smem();
                __syncwarp();
                mbar_arrive_if(lane == 0, cur.b + B_PV);
                if (s == NSEG - 1) break;
            }
            po += (int)nx.o - (int)cur.o;
            pm0 += (int)cur.o - (int)p1.o;
            mt = msum - mt;
            float acc[16];
            mbar_wait(cur.b + B_VA, cur.ph, dl);
            token_gemm<0, TGA0>(acc, wt, sb + OFF_XT + ((s + 1) & 3) * XT_BYTES);
            mbar_wait(cur.b + B_VB, cur.ph, dl);
            token_gemm<TGA0, 28>(acc, wt, sb + OFF_XT + ((s + 1) & 3) * XT_BYTES);
            stsm4(st_off + nx.o, pack_bf(acc[0], acc[1]), pack_bf(acc[2], acc[3]), pack_bf(acc[4], acc[5]), pack_bf(acc[6], acc[7]));
            stsm4(st_off + nx.o + 256, pack_bf(acc[8], acc[9]), pack_bf(acc[10], acc[11]), pack_bf(acc[12], acc[13]), pack_bf(acc[14], acc[15]));
            __syncwarp();
            mbar_arrive_if(lane == 0, nx.b + B_KQ);
            p1 = cur; cur = nx;
        }
        cluster_sync_relaxed();
    } else if (wg == 1) {
        mem_share();
        asm volatile("setmaxnreg.inc.sync.aligned.u32 176;");
        uint32_t wt[112];
        prologue_weights<1>(wt, sb, lane, dl, mem_store);
        asm volatile("barrier.cluster.wait.aligned;" ::: "memory");
        bar_sync(6, 256);
        asm volatile("barrier.cluster.arrive.relaxed.aligned;" ::: "memory");
        const uint32_t st_off = ub + U_V + (2 * w + ((lane >> 3) & 1)) * VP + (lane >> 4) * 128 + (lane & 7) * 16;
        const uint32_t vs_off = ub + U_V + 2 * w * VP + 512 + lane * 4;
        const uint32_t ex_off = opaque(sb + OFF_EX + lane * 16, lane);
#pragma unroll
        for (int i = 0; i < 8; i++) sts32(vs_off + 128 + (i >> 1) * 16384 + (i & 1) * VP, 0u);
        const uint32_t rs_dst0 = mapa(ub + U_RS + h * 64 + (g & 3) * 16 + t * 4, 4 * w + (g >> 2));
        const uint32_t rs_dst1 = mapa(ub + U_RS + h * 64 + (g & 3) * 16 + t * 4, 4 * w + 2 + (g >> 2));
        const uint32_t rs_bar0 = mapa(bars + B_RS, 4 * w + (g >> 2));
        const uint32_t rs_bar1 = mapa(bars + B_RS, 4 * w + 2 + (g >> 2));
        uint32_t mt = opaque(sb + OFF_MT + lane * 16, lane);
        const uint32_t ONES = 0x3F803F80u;
        uint32_t vx[8];
        {
            float acc[16];
            mbar_wait(bars + B_X, 0, dl);
            token_gemm<0, 28>(acc, wt, sb + OFF_XT);
#pragma unroll
            for (int i = 0; i < 8; i++) vx[i] = pack_bf(acc[2 * i], acc[2 * i + 1]);
            stsm4(st_off, vx[0], vx[1], vx[2], vx[3]);
            stsm4(st_off + 256, vx[4], vx[5], vx[6], vx[7]);
        }
        bar_sync(0, 512);
        asm volatile("barrier.cluster.wait.aligned;" ::: "memory");
        const unsigned char* p = cblk(comm, ID_SMM + h, (int)lds32(bars + P_SIDE)) + w * 1024 + lane * 4;
        Cur cur = c0.next(bars);
#pragma unroll 1
        for (int s = 0; s < NSEG; s++) {
            const Cur nx = cur.next(bars);
            {
                const uint32_t T = cur.ph - 1u;
                const uint32_t d0a = opaque(rs_dst0 + cur.o, lane), d1a = opaque(rs_dst1 + cur.o, lane);
                const uint32_t b0a = opaque(rs_bar0 + (cur.o >> 7), lane), b1a = opaque(rs_bar1 + (cur.o >> 7), lane);
                const uint32_t exa = opaque(ex_off + (cur.o >> 5), lane);
                mbar_wait(cur.b + B_KF, cur.ph, dl);
                const uint32_t tpoll = clk() + D_SMM;
                float o[4];
                mem_gemm(o, wt, mt);
                const uint32_t vm0 = pack_bf(o[0], o[1]), vm1 = pack_bf(o[2], o[3]);
                mbar_arrive_if(lane == 0 && vm0 != 0x7fc17fc2u, cur.b + B_VA);
                spin_until(tpoll);
                uint32_t r[7];
#pragma unroll
                for (int i = 0; i < 7; i++) r[i] = ldg_rlx32(p + i * 128);
                sts32(vs_off + cur.o, vm0);
                sts32(vs_off + cur.o + VP, vm1);
                fence_async_smem();
                if (s == NSEG - 1) { __syncwarp(); mbar_arrive_if(lane == 0, cur.b + B_PV); break; }
                mbar_wait(cur.b + B_EX, cur.ph, dl);
                uint4 e0;
                ldsm4(&e0.x, exa);
                float nx4[4], zx[4], n2[4], z2[4], s0, s1;
                ZERO4(nx4); ZERO4(zx);
                mma16816v(zx, ONES, ONES, ONES, ONES, e0.x, e0.y);
                mma16816v(nx4, vx[0], vx[1], vx[2], vx[3], e0.x, e0.y);
                mma16816v(zx, ONES, ONES, ONES, ONES, e0.z, e0.w);
                mma16816v(nx4, vx[4], vx[5], vx[6], vx[7], e0.z, e0.w);
                const uint32_t uns = or3(e0.x, e0.y, e0.z) | e0.w;
                mbar_wait(nx.b + B_X, nx.ph, dl);
                mbar_arrive_if(lane == 0 && __float_as_uint(nx4[0] + zx[0]) != 0x7fc12345u, cur.b + B_VB);
                while (true) {
                    s0 = SUM7_LO(r); s1 = SUM7_HI(r);
                    const uint32_t flag = (BAD7(r, T) & 1u) | ((fmaxf(fabsf(s0), fabsf(s1)) <= SAFE ? uns : ~0u) & 0x80000000u);
                    const uint32_t pk = pack_bf(ex2(s0 * LOG2E), ex2(s1 * LOG2E));
                    const bool fast = __all_sync(0xffffffffu, flag == 0);
#pragma unroll
                    for (int i = 0; i < 4; i++) { n2[i] = nx4[i]; z2[i] = zx[i]; }
                    mma1688v(z2, ONES, ONES, pk);
                    mma1688v(n2, vm0, vm1, pk);
                    if (fast) break;
                    if (__all_sync(0xffffffffu, (flag & 1u) == 0) || expired(dl)) {
                        float e[8];
#pragma unroll
                        for (int i = 0; i < 4; i++) {
                            const uint2 q = lds64(mt + 7168 + i * 256 - lane * 8);
                            e[2 * i] = __uint_as_float(q.x); e[2 * i + 1] = __uint_as_float(q.y);
                        }
                        float mm = fmaxf(s0, s1);
#pragma unroll
                        for (int i = 0; i < 8; i++) mm = fmaxf(mm, e[i]);
                        mm = fmaxf(mm, shx(mm, 1));
                        mm = fmaxf(mm, shx(mm, 2));
                        const float nm = -mm * LOG2E;
#pragma unroll
                        for (int i = 0; i < 8; i++) e[i] = ex2(fmaf(e[i], LOG2E, nm));
                        e0 = make_uint4(pack_bf(e[0], e[1]), pack_bf(e[2], e[3]), pack_bf(e[4], e[5]), pack_bf(e[6], e[7]));
                        const uint32_t pq = pack_bf(ex2(fmaf(s0, LOG2E, nm)), ex2(fmaf(s1, LOG2E, nm)));
                        ZERO4(n2); ZERO4(z2);
                        mma1688(n2, vm0, vm1, pq);
                        mma1688(z2, ONES, ONES, pq);
                        mma16816(z2, ONES, ONES, ONES, ONES, e0.x, e0.y);
                        mma16816(n2, vx[0], vx[1], vx[2], vx[3], e0.x, e0.y);
                        mma16816(z2, ONES, ONES, ONES, ONES, e0.z, e0.w);
                        mma16816(n2, vx[4], vx[5], vx[6], vx[7], e0.z, e0.w);
                        break;
                    }
#pragma unroll
                    for (int i = 0; i < 7; i++) ldg_rlx32_if(r[i], (r[i] ^ T) & 1u, p + i * 128);
                }
                const float i0 = rcp(z2[0]), i1 = rcp(z2[1]);
                st_async32(d0a, b0a, pack_bf(n2[0] * i0, n2[1] * i1));
                st_async32(d1a, b1a, pack_bf(n2[2] * i0, n2[3] * i1));
                __syncwarp();
                mbar_arrive_if(lane == 0, cur.b + B_PV);
            }
            p += (int)nx.o - (int)cur.o;
            mt = msum - mt;
            float acc[16];
            mbar_wait(cur.b + B_PUB, cur.ph, dl);
            token_gemm<0, 28>(acc, wt, sb + OFF_XT + ((s + 1) & 3) * XT_BYTES);
#pragma unroll
            for (int i = 0; i < 8; i++) vx[i] = pack_bf(acc[2 * i], acc[2 * i + 1]);
            mbar_wait(cur.b + B_XD, cur.ph, dl);
            stsm4(st_off + nx.o, vx[0], vx[1], vx[2], vx[3]);
            stsm4(st_off + nx.o + 256, vx[4], vx[5], vx[6], vx[7]);
            cur = nx;
        }
        cluster_sync_relaxed();
    } else if (wg == 2) {
        asm volatile("setmaxnreg.dec.sync.aligned.u32 56;");
        init_share();
        ln_share();
        asm volatile("barrier.cluster.wait.aligned;" ::: "memory");
        if (lane == 0) {
            if (w == 0) {
                const unsigned target = (ldg_rlx32(&g_epoch) + 1) * NCHAIN;
                asm volatile("red.release.gpu.global.add.u32 [%0], 1;" :: "l"(&g_start_cnt) : "memory");
                while ((int)(ldg_acq32(&g_start_cnt) - target) < 0) { if (expired(dl)) break; }
                fence_async_all();
                mbar_expect(bars + B_X, XT_BYTES);
                if (h < 7) tma_load_mc(sb + OFF_XT + h * 4096, &mXn, h * 64, 0, bars + B_X, 0xffff);
            } else if (w == 1) {
                unsigned* q0 = reinterpret_cast<unsigned*>(cblk(comm, ID_PROBE, 0) + cta * 32);
                unsigned* q1 = reinterpret_cast<unsigned*>(cblk(comm, ID_PROBE, 1) + cta * 32);
                stg_rlx32(q0, 0u); stg_rlx32(q1, 0u);
                unsigned b0 = ~0u, b1 = ~0u, acc = 0;
#pragma unroll 1
                for (int r = 0; r < 6; r++) {
                    const unsigned k0 = clk(); acc += atom_add(q0 + (acc >> 20)); const unsigned k1 = clk() + (acc >> 20);
                    acc += atom_add(q1 + (acc >> 20)); const unsigned k2 = clk() + (acc >> 20);
                    b0 = min(b0, k1 - k0); b1 = min(b1, k2 - k1);
                }
#pragma unroll 1
                for (int r = 0; r < CSZ; r++) st_async32(mapa(bars + P_VAL + h * 4, r), mapa(bars + P_VOTE, r), b0 < b1 ? 0u : 1u);
                mbar_wait(bars + P_VOTE, 0, dl);
                uint32_t votes = 0;
#pragma unroll 1
                for (int r = 0; r < CSZ; r++) votes += lds32(bars + P_VAL + r * 4);
                sts32(bars + P_SIDE, votes > CSZ / 2 ? 1u : 0u);
            }
        }
        __syncwarp();
        asm volatile("barrier.cluster.arrive.relaxed.aligned;" ::: "memory");
        bar_sync(0, 512);
        asm volatile("barrier.cluster.wait.aligned;" ::: "memory");
        const int side = (int)lds32(bars + P_SIDE);
        unsigned char* psmx = cblk(comm, ID_SMX + h, side) + w * 128 + lane * 4;
        const int dsmx = (int)(cblk(comm, ID_SMX + h, side ^ 1) - cblk(comm, ID_SMX + h, side)) + (int)j * 512;
        const int v0 = 64 * j + 4 * h;
        unsigned char* po = cblk(comm, ID_M + (v0 >> 8), lane >> 4) + (v0 & 255) * 16 + (lane & 15) * 4;
        const uint32_t kb_off = opaque(ub + U_K + (lane >> 3) * KP + w * 128 + (lane & 7) * 16, lane), rs_off = opaque(ub + U_RS + lane * 16, lane);
        const uint32_t ex_off = opaque(sb + OFF_EX + w * 128 + lane * 4, lane);
        uint32_t mt = opaque(sb + OFF_MT + lane * 16, lane);
        const uint32_t mj = 1024 * j, j512 = 512 * j;
        Cur cur = c0.next(bars);
#pragma unroll 1
        for (int s = 0; s < NSEG; s++) {
            const uint32_t tg = cur.ph ^ 1u;
            uint32_t kb[8], ma[8];
            mbar_wait(cur.b + B_KQ, cur.ph, dl);
            ldsm4t(kb, kb_off + cur.o);
            ldsm4t(kb + 4, kb_off + cur.o + 4 * KP);
            bar_sync(4, 256);
            ldsm4t(ma, mt + mj);
            ldsm4t(ma + 4, mt + mj + 512);
            const uint32_t wd = put_tag(mem_scores(ma, kb), tg);
            stg_rlx32(psmx + dsmx, wd);
            stg_rlx32(psmx + j512, wd);
            const Cur nx = cur.next(bars);
            if (s < NSEG - 1) {
                const uint32_t T = 0u - tg;
                uint32_t r[7];
                spin(D_SMX);
#pragma unroll
                for (int i = 0; i < 7; i++) r[i] = ldg_rlx32(psmx + i * 512);
                while (true) {
                    const float s0 = SUM7_LO(r), s1 = SUM7_HI(r);
                    const bool ok = __all_sync(0xffffffffu, (BAD7(r, T) & 1u) == 0);
                    const uint32_t ew = pack_bf(ex2(s0 * LOG2E), ex2(s1 * LOG2E));
                    sts64(mt + 7168 + w * 256 - lane * 8, __float_as_uint(s0), __float_as_uint(s1));
                    sts32(ex_off + (cur.o >> 5), fmaxf(fabsf(s0), fabsf(s1)) <= SAFE ? ew : ~0u);
                    if (ok) break;
#pragma unroll
                    for (int i = 0; i < 7; i++) ldg_rlx32_if(r[i], (r[i] ^ T) & 1u, psmx + i * 512);
                    if (expired(dl)) break;
                }
                __syncwarp();
                mbar_arrive_if(lane == 0, cur.b + B_EX);
            }
            psmx += (int)nx.o - (int)cur.o;
            mt = msum - mt;
            if (w == 0) {
                uint32_t md = 0;
                if (s < NSEG - 1) {
                    const uint32_t src = rs_off + cur.o;
                    mbar_wait(cur.b + B_RS, cur.ph, dl);
                    uint32_t r[8];
                    ldsm4(r, src);
                    ldsm4(r + 4, src + 512);
                    float lo = ((bf_lo(r[0]) + bf_lo(r[1])) + (bf_lo(r[2]) + bf_lo(r[3]))) + ((bf_lo(r[4]) + bf_lo(r[5])) + (bf_lo(r[6]) + bf_lo(r[7])));
                    float hi = ((bf_hi(r[0]) + bf_hi(r[1])) + (bf_hi(r[2]) + bf_hi(r[3]))) + ((bf_hi(r[4]) + bf_hi(r[5])) + (bf_hi(r[6]) + bf_hi(r[7])));
                    lo += shx(lo, 16); hi += shx(hi, 16);
                    md = pack_bf(lo, hi);
                }
                md = put_tag(md, tg);
                stg_rlx32(po, md);
                sts32(cur.b + B_TPUB, clk() + D_M);
                mbar_arrive_if(lane == 0, cur.b + B_PUB);
                if (lane == 0 && s < NSEG - 1) mbar_expect(cur.b + B_RS, 1024);
                __syncwarp();
            }
            po += (int)nx.o - (int)cur.o;
            cur = nx;
        }
        cluster_sync_relaxed();
    } else {
        asm volatile("setmaxnreg.dec.sync.aligned.u32 96;");
        asm volatile("barrier.cluster.arrive.relaxed.aligned;" ::: "memory");
        if (w == 3) bar_sync(5, 384); else asm volatile("bar.arrive 5, 384;" ::: "memory");
        if (w < 3) ln_share();
        asm volatile("barrier.cluster.wait.aligned;" ::: "memory");
        if (w == 3 && lane == 0) {
#pragma unroll 1
            for (int i = 8; i < 32; i++) {
                const int slot = i & 7, q = i >> 1;
                mbar_wait(bars + P_STE + slot * 8, ((i >> 3) - 1) & 1, dl);
                mbar_expect(bars + P_STF + slot * 8, ST_BYTES);
                tma_load_once(sb + OFF_XT + XT_BYTES + slot * ST_BYTES, (i & 1) ? &mWv : &mWk, h * 256 + (q & 3) * 64, (q >> 2) * 112, bars + P_STF + slot * 8);
            }
        }
        __syncwarp();
        cluster_sync_relaxed();
        if (w == 0 && lane == 0) {
            mbar_wait(bars + B_X, 0, dl);
            fence_async_all();
#pragma unroll 1
            for (int q = 1; q < 4; q++) {
                mbar_expect(bars + q * 128 + B_X, XT_BYTES);
                if (h < 7) tma_load_mc(sb + OFF_XT + q * XT_BYTES + h * 4096, &mXn, h * 64, q * 32, bars + q * 128 + B_X, 0xffff);
            }
        }
        __syncwarp();
        bar_sync(0, 512);
        const int side = (int)lds32(bars + P_SIDE);
        const uint32_t stag = (ldg_rlx32(&g_epoch) & 1u) ^ 1u;
        unsigned char* psx = g_sx + h * (4 * 4480);
        unsigned char* pp = cblk(comm, ID_P + h, side);
        const int dpp = (int)(cblk(comm, ID_P + h, side ^ 1) - pp);
        const uint32_t rsx_dst = mapa(ub + U_RSX + h * 256 + w * 64 + g * 8, t), rsx_bar = mapa(bars + B_RSX, t);
        const uint32_t rstep = mapa(bars, 4) - mapa(bars, 0);
        sts32(sb + OFF_P + w * VP + 640 + lane * 4, 0u);
        int nt = (j + 1) % 7;
        Cur p3 = c0, p2 = c0, p1 = c0, cur = c0.next(bars);
#pragma unroll 1
        for (int s = 0; s < NSEG + 4; s++) {
            nt = nt >= 4 ? nt - 4 : nt + 3;
            if (s < NSEG) mbar_wait(cur.b + B_KF, cur.ph, dl);
            if (s >= 4 && w < 2) {
                const int sg = s - 4;
                const uint32_t rb = bars + (sg & 3) * 128 + B_RSX;
                const uint32_t src = ub + U_RSX + (sg & 3) * 16384 + w * 128 + (lane >> 3) * 256 + (lane & 7) * 16;
                mbar_wait(rb, (sg >> 2) & 1, dl);
                uint32_t r[16];
#pragma unroll
                for (int i = 0; i < 4; i++) ldsm4(r + 4 * i, src + i * 1024);
                float lo[4], hi[4];
#pragma unroll
                for (int i = 0; i < 4; i++) {
                    lo[i] = (bf_lo(r[i]) + bf_lo(r[4 + i])) + (bf_lo(r[8 + i]) + bf_lo(r[12 + i]));
                    hi[i] = (bf_hi(r[i]) + bf_hi(r[4 + i])) + (bf_hi(r[8 + i]) + bf_hi(r[12 + i]));
                }
                uint32_t* o = reinterpret_cast<uint32_t*>(g_sw) + (sg * 32 + 2 * h) * D_ + 64 * j + 32 * w + (lane & 16) + ((lane & 15) >> 1) + (lane & 1) * 8;
                stg_rlx32(o, put_tag(__float_as_uint((lo[0] + lo[1]) + (lo[2] + lo[3])), stag));
                stg_rlx32(o + D_, put_tag(__float_as_uint((hi[0] + hi[1]) + (hi[2] + hi[3])), stag));
                mbar_expect_if(lane == 0, rb, 2048);
            }
            const bool have_p = s >= 3 && s < NSEG + 3;
            if (have_p) {
                const uint32_t T = p3.ph - 1u, pa = sb + OFF_P + w * VP;
                uint32_t q[5];
                if (s <= NSEG) {
                    mbar_wait(p3.b + B_P, p3.ph, dl);
                    ldsm4(q, pa + lane * 16);
                    q[4] = lds32(pa + 512 + lane * 4);
                } else {
                    q[0] = q[1] = q[2] = q[3] = q[4] = p3.ph;
                }
                while (__any_sync(0xffffffffu, (or3(bad2(q[0], q[1], T), bad2(q[2], q[3], T), q[4] ^ T) & 1u) != 0)) {
#pragma unroll
                    for (int k = 0; k < 5; k++) q[k] = ldg_rlx32(pp + p3.o + w * VP + k * 128 + lane * 4);
#pragma unroll
                    for (int k = 0; k < 5; k++) sts32(pa + k * 128 + lane * 4, q[k]);
                    fence_async_smem();
                    if (expired(dl)) break;
                }
            }
            if (s < NSEG) {
                __syncwarp();
                mbar_arrive_if(lane == 0, cur.b + B_PV);
                mbar_wait(cur.b + B_PV, cur.ph, dl);
            } else {
                bar_sync(3, 128);
            }
            const bool job = nt < 4 && s >= 1 && s <= NSEG;
            if (w == 2 && s < NSEG) {
                if (lane == 0) {
                    if (job) {
                        mbar_expect(p1.b + B_SX, SX_BYTES);
                        bulk_load(sb + OFF_SX, psx + (p1.o >> 14) * (64 * 4480) + nt * 4480, SX_BYTES, p1.b + B_SX);
                    } else if (s >= 1) {
                        mbar_arrive(p1.b + B_SX);
                    }
                    if (s >= 2 && s + 2 < NSEG) {
                        const int q = (s + 2) & 3;
                        mbar_expect(bars + q * 128 + B_X, XT_BYTES);
                        if (h < 7) tma_load_mc(sb + OFF_XT + q * XT_BYTES + h * 4096, &mXn, h * 64, (s + 2) * 32, bars + q * 128 + B_X, 0xffff);
                    }
                }
                __syncwarp();
            }
            float c[20], d[16];
            const uint32_t alo = desc_lo(sb + OFF_XT + (s & 3) * XT_BYTES + j * 4096);
            const uint64_t dk = desc_plain(ub + U_K + cur.o, KP, 128), dv = desc_plain(ub + U_V + p3.o, 128, VP), dp = desc_plain(sb + OFF_P, 128, VP);
#pragma unroll
            for (int i = 0; i < 20; i++) c[i] = 0.f;
#pragma unroll
            for (int i = 0; i < 16; i++) d[i] = 0.f;
            if (s < NSEG) mbar_wait(cur.b + B_PUB, cur.ph, dl);
            wg_fence();
#pragma unroll
            for (int kk = 0; kk < 4; kk++) wg_ss_n40<0, 1>(c, desc_at(alo, kk * 32), dk + kk * (2 * KP / 16), kk > 0);
#pragma unroll
            for (int kk = 0; kk < 3; kk++) wg_ss_n32<0, 0>(d, dv + kk * 16, dp + kk * 16, kk > 0);
            wg_commit();
            wg_wait<0>();
            bar_sync(3, 128);
            if (s < NSEG) {
                mbar_arrive_if(lane == 0, cur.b + B_XD);
                if (w < 2) {
                    const uint32_t tg = cur.ph ^ 1u;
                    unsigned char* qa = psx + (cur.o >> 14) * (64 * 4480) + 2 * w * 4480 + j * 640 + lane * 4;
#pragma unroll
                    for (int k = 0; k < 5; k++) {
                        const int ci = k == 0 ? 16 : 4 * (k - 1);
                        if (k < 4) stg_rlx32_if(k <= 2 * w + 1, qa + k * 128, put_tag(pack_bf(c[ci], c[ci + 1]), tg));
                        stg_rlx32_if(k <= 2 * w + 2, qa + 4480 + k * 128, put_tag(pack_bf(c[ci + 2], c[ci + 3]), tg));
                    }
                } else if (w == 2 && lane == 0 && s >= 2) {
                    mbar_expect(p2.b + B_P, 3072);
                    bulk_load(sb + OFF_P, pp + p2.o, 3072, p2.b + B_P);
                }
                __syncwarp();
            }
            if (have_p) {
                if (s < NSEG - 1) {
                    const uint32_t os = sb + OFF_OS + (s & 3) * 4352;
#pragma unroll
                    for (int q = 0; q < 4; q++) sts64(os + (4 * q + t) * 272 + w * 64 + g * 8, pack_bf(d[4 * q], d[4 * q + 1]), pack_bf(d[4 * q + 2], d[4 * q + 3]));
                    fence_async_smem();
                    bar_sync(3, 128);
                    if (w == 2 && lane < 16) bulk_s2c(mapa(ub + U_RSX + p3.o + h * 256, lane), os + lane * 272, 256, mapa(bars + B_RSX + (p3.o >> 7), lane));
                    __syncwarp();
                } else {
#pragma unroll
                    for (int q = 0; q < 4; q++)
                        st_async64(rsx_dst + p3.o + q * rstep, rsx_bar + (p3.o >> 7) + q * rstep, pack_bf(d[4 * q], d[4 * q + 1]), pack_bf(d[4 * q + 2], d[4 * q + 3]));
                }
            }
            if (w == 3 && job) {
                const uint32_t T = p1.ph - 1u;
                uint32_t r[7][5];
                if (s < NSEG) {
                    const uint32_t sx = sb + OFF_SX;
                    uint32_t q[8];
                    mbar_wait(p1.b + B_SX, p1.ph, dl);
#pragma unroll
                    for (int i = 0; i < 7; i++) ldsm4(r[i], sx + i * 640 + lane * 16);
                    ldsm4(q, sx + 512 + (lane >> 3) * 640 + (lane & 7) * 16);
                    ldsm4(q + 4, sx + 512 + min(4 + (lane >> 3), 6) * 640 + (lane & 7) * 16);
#pragma unroll
                    for (int i = 0; i < 7; i++) r[i][4] = q[i];
                } else {
#pragma unroll
                    for (int i = 0; i < 7; i++) r[i][0] = r[i][1] = r[i][2] = r[i][3] = r[i][4] = p1.ph;
                }
                while (true) {
                    uint32_t b0 = bad2(r[6][0], r[6][1], T), b1 = r[6][2] ^ T, b2 = r[6][3] ^ T, b3 = r[6][4] ^ T;
#pragma unroll
                    for (int i = 0; i < 6; i += 2) {
                        b0 = or3(b0, bad2(r[i][0], r[i][1], T), bad2(r[i + 1][0], r[i + 1][1], T));
                        b1 |= bad2(r[i][2], r[i + 1][2], T); b2 |= bad2(r[i][3], r[i + 1][3], T); b3 |= bad2(r[i][4], r[i + 1][4], T);
                    }
                    b0 = or3(b0, nt >= 1 ? b1 : 0u, nt >= 2 ? b2 : 0u) | (nt == 3 ? b3 : 0u);
                    if (__all_sync(0xffffffffu, (b0 & 1u) == 0)) break;
                    if (expired(dl)) break;
                    const unsigned char* p = psx + (p1.o >> 14) * (64 * 4480) + nt * 4480 + lane * 4;
#pragma unroll
                    for (int i = 0; i < 35; i++) r[i / 5][i % 5] = ldg_rlx32(p + i * 128);
                }
                float e[10];
                const int lim = 8 * nt + g - 2 * t;
#pragma unroll
                for (int k = 0; k < 5; k++) {
                    const uint32_t q[7] = {r[0][k], r[1][k], r[2][k], r[3][k], r[4][k], r[5][k], r[6][k]};
                    const float lo = SUM7_LO(q), hi = SUM7_HI(q);
                    e[2 * k] = k == 0 ? lo : fsel(8 * (k - 1) <= lim, lo, -INFINITY);
                    e[2 * k + 1] = k == 0 ? hi : fsel(8 * (k - 1) + 1 <= lim, hi, -INFINITY);
                }
                float mx = fmaxf(fmaxf(fmaxf(e[0], e[1]), fmaxf(e[2], e[3])), fmaxf(fmaxf(fmaxf(e[4], e[5]), fmaxf(e[6], e[7])), fmaxf(e[8], e[9])));
                mx = fmaxf(mx, shx(mx, 1));
                mx = fmaxf(mx, shx(mx, 2));
                const float nm = -mx * LOG2E;
#pragma unroll
                for (int i = 0; i < 10; i++) e[i] = ex2(fmaf(e[i], LOG2E, nm));
                float z = (((e[0] + e[1]) + (e[2] + e[3])) + ((e[4] + e[5]) + (e[6] + e[7]))) + (e[8] + e[9]);
                z += shx(z, 1);
                z += shx(z, 2);
                const float inv = rcp(z);
                unsigned char* po = pp + p1.o + nt * VP + lane * 4;
#pragma unroll
                for (int i = 0; i < 5; i++) {
                    const uint32_t pv = put_tag(pack_bf(e[2 * i] * inv, e[2 * i + 1] * inv), p1.ph ^ 1u);
                    stg_rlx32(po + (i == 0 ? 512 : (i - 1) * 128) + dpp, pv);
                    stg_rlx32(po + (i == 0 ? 512 : (i - 1) * 128), pv);
                }
            }
            p3 = p2; p2 = p1; p1 = cur; cur = cur.next(bars);
        }
        cluster_sync_relaxed();
    }
}

constexpr uint32_t PACE3 = 680, PACE4 = 1950;
constexpr int PP = 14336;
constexpr int NW = 11;
constexpr int M_P = 0, M_STG = 7 * PP, M_W = M_STG + 3 * 13312, M_BAR = M_W + NW * 8192;
constexpr int ML_SMEM = M_BAR + 512 + 1024;
enum { MB_WF = 0, MB_WE = NW, MB_HF = 2 * NW, MB_HE = 2 * NW + 7, MB_X = 2 * NW + 14, MB_RDY = 2 * NW + 15, MB_NUM = 2 * NW + 16 };

template<int N> struct WgSel;
template<> struct WgSel<112> { static __device__ __forceinline__ void run(float (&d)[56], uint64_t a, uint64_t b, int sc) { wg_ss_n112<1>(d, a, b, sc); } };
template<> struct WgSel<104> { static __device__ __forceinline__ void run(float (&d)[52], uint64_t a, uint64_t b, int sc) { wg_ss_n104<1>(d, a, b, sc); } };

struct WRing { int s0, s1, slot, ph; __device__ __forceinline__ void next() { if (++slot == s1) { slot = s0; ph ^= 1; } } };
__device__ __forceinline__ WRing make_ring(int k, int ph) { WRing r; r.s0 = k == 0 ? 0 : 2 + 3 * k; r.s1 = 5 + 3 * k; r.slot = r.s0; r.ph = ph; return r; }
template<int NT, int N, bool RING>
__device__ __forceinline__ void mlp_gemm(float (&acc)[NT][N / 2], uint32_t sb, WRing& rg, int nkb, int lane, uint32_t dl) {
    const uint32_t bars = sb + M_BAR;
    uint32_t prev = 0, prevh = 0;
#pragma unroll 1
    for (int kb = 0; kb < nkb; kb++) {
        const int hs = RING ? kb % 7 : kb;
        if (RING) mbar_wait(bars + (MB_HF + hs) * 8, (kb / 7) & 1, dl);
        const uint32_t blo = desc_lo(sb + M_P + hs * PP);
#pragma unroll
        for (int i = 0; i < NT; i++) {
            const int slot = rg.slot;
            const uint32_t alo = desc_lo(sb + M_W + slot * 8192);
            mbar_wait(bars + (MB_WF + slot) * 8, rg.ph, dl);
            rg.next();
            wg_fence();
#pragma unroll
            for (int ks = 0; ks < 4; ks++) WgSel<N>::run(acc[i], desc_at(alo, ks * 2048), desc_at(blo, ks * 32), (kb | ks) != 0);
            wg_commit();
            wg_wait<1>();
            mbar_arrive_if(lane == 0 && prev != 0, prev);
            if (RING && i == 0) mbar_arrive_if(lane == 0 && prevh != 0, prevh);
            prev = bars + (MB_WE + slot) * 8;
        }
        prevh = bars + (MB_HE + hs) * 8;
    }
    wg_wait<0>();
    mbar_arrive_if(lane == 0, prev);
}
template<bool GELU>
__device__ __forceinline__ void mlp_store(const float (&a)[52], uint32_t blk, int w, int lane) {
    const uint32_t ad0 = blk + (8 * (lane >> 4) + (lane & 7)) * 128 + (((2 * w + ((lane >> 3) & 1)) ^ (lane & 7)) << 4);
#pragma unroll
    for (int i = 0; i < 13; i += 2) {
        uint32_t r[4];
#pragma unroll
        for (int k = 0; k < 4; k++) {
            if (4 * i + 2 * k < 52) {
                r[k] = pack_bf(a[4 * i + 2 * k], a[4 * i + 2 * k + 1]);
                if (GELU) r[k] = pack_bf(gelu_tanh(bf_lo(r[k])), gelu_tanh(bf_hi(r[k])));
            }
        }
        if (i < 12) stsm4t(ad0 + i * 1024, r[0], r[1], r[2], r[3]); else stsm2t(ad0 + i * 1024, r[0], r[1]);
    }
}
__device__ __forceinline__ uint32_t prow(uint32_t sb, int r, int lane) { return sb + M_P + r * 128 + (((lane >> 2) ^ (r & 7)) << 4) + (lane & 3) * 4; }
__device__ __forceinline__ void mlp_rows(uint32_t sb, uint32_t* x1s, int cw, int lane) {
    const int T0 = blockIdx.x * MT;
    const uint32_t* xn = reinterpret_cast<const uint32_t*>(g_xn) + lane;
    uint32_t u[7];
#pragma unroll
    for (int i = 0; i < 7; i++) u[i] = __ldcg(xn + (T0 + cw) * (D_ / 2) + 32 * i);
    bar_sync(1, 384);
#pragma unroll 1
    for (int r = cw; r < MT; r += 12) {
        uint32_t v[7];
        const uint32_t pr = prow(sb, r, lane);
#pragma unroll
        for (int i = 0; i < 7; i++) {
            asm("add.rn.bf16x2 %0, %1, %2;" : "=r"(v[i]) : "r"(u[i]), "r"(lds32(pr + i * PP)));
            u[i] = __ldcg(xn + min(T0 + r + 12, S_ - 1) * (D_ / 2) + 32 * i);
            x1s[r * (D_ / 2) + 32 * i] = v[i];
        }
        ln_row(v);
#pragma unroll
        for (int i = 0; i < 7; i++) sts32(pr + i * PP, v[i]);
    }
}
__device__ __forceinline__ void mlp_final(uint32_t sb, const uint32_t* x1s, const bf16* __restrict__ x, bf16* __restrict__ out, int cw, int lane, uint32_t stag, uint32_t dl) {
    const int T0 = blockIdx.x * MT, n = min(MT, S_ - T0);
    const uint32_t T = 0u - stag;
    const uint32_t* xg = reinterpret_cast<const uint32_t*>(x + T0 * D_) + lane;
    uint32_t u[7], xv[7];
#pragma unroll
    for (int i = 0; i < 7; i++) { u[i] = __ldcg(x1s + cw * (D_ / 2) + 32 * i); xv[i] = __ldg(xg + cw * (D_ / 2) + 32 * i); }
    bar_sync(1, 384);
#pragma unroll 1
    for (int r = cw; r < n; r += 12) {
        const uint32_t pr = prow(sb, r, lane);
        const int rn = min(r + 12, n - 1);
#pragma unroll
        for (int i = 0; i < 7; i++) {
            uint32_t y;
            asm("add.rn.bf16x2 %0, %1, %2;" : "=r"(y) : "r"(u[i]), "r"(lds32(pr + i * PP)));
            sts32(sb + M_STG + (r * 7 + i) * 128 + lane * 4, xv[i]);
            u[i] = __ldcg(x1s + rn * (D_ / 2) + 32 * i); xv[i] = __ldg(xg + rn * (D_ / 2) + 32 * i);
            const float y0 = bf_lo(y), y1 = bf_hi(y);
            sts32(pr + i * PP, pack_bf(y0 * rcp(1.0f + ex2(-y0 * LOG2E)), y1 * rcp(1.0f + ex2(-y1 * LOG2E))));
        }
    }
#pragma unroll 1
    for (int r0 = cw; r0 < n; r0 += 36) {
        uint2 sv[3][7];
        const int rl = min(r0 + 24, r0 + (n - 1 - r0) / 12 * 12);
        const int re = max(T0 + rl - 32, 0);
        while (((ldg_rlx32(g_sw + re * (D_ / 2)) ^ T) & 1u) != 0 && !expired(dl)) __nanosleep(300);
        while (((ldg_rlx32(g_sw + (T0 + rl) * (D_ / 2)) ^ T) & 1u) != 0 && !expired(dl)) spin(64);
        while (true) {
            uint32_t bad = 0;
#pragma unroll
            for (int a = 0; a < 3; a++)
#pragma unroll
                for (int i = 0; i < 7; i++) sv[a][i] = ldg_rlx64(g_sw + (T0 + min(r0 + 12 * a, rl)) * (D_ / 2) + lane + 32 * i);
#pragma unroll
            for (int a = 0; a < 3; a++)
#pragma unroll
                for (int i = 0; i < 7; i++) bad |= bad2(sv[a][i].x, sv[a][i].y, T);
            if (__all_sync(0xffffffffu, (bad & 1u) == 0) || expired(dl)) break;
        }
#pragma unroll 1
        for (int a = 0; a < 3; a++) {
            const int r = min(r0 + 12 * a, rl);
            const uint32_t pr = prow(sb, r, lane);
#pragma unroll
            for (int i = 0; i < 7; i++) {
                const uint32_t gq = lds32(pr + i * PP), xq = lds32(sb + M_STG + (r * 7 + i) * 128 + lane * 4);
                const uint32_t sp = pack_bf(__uint_as_float(sv[0][i].x), __uint_as_float(sv[0][i].y));
                uint32_t pd;
                asm("mul.rn.bf16x2 %0, %1, %2;" : "=r"(pd) : "r"(sp), "r"(gq));
                asm("add.rn.bf16x2 %0, %1, %2;" : "=r"(pd) : "r"(xq), "r"(pd));
                reinterpret_cast<uint32_t*>(out + (T0 + r) * D_)[lane + 32 * i] = pd;
                sv[0][i] = sv[1][i]; sv[1][i] = sv[2][i];
            }
        }
    }
}
template<int NT, int NA> __device__ __forceinline__ void rotate_acc(float (&acc)[NT][NA]) {
#pragma unroll
    for (int i = 0; i + 1 < NT; i++)
#pragma unroll
        for (int k = 0; k < NA; k++) acc[i][k] = acc[i + 1][k];
}

template<int NT>
__device__ __forceinline__ void mlp_consumer(const CUtensorMap* mH, const bf16* __restrict__ x, bf16* __restrict__ out, uint32_t sb, int k, int w, int lane,
                                             uint32_t stag, uint32_t dl) {
    const int T0 = blockIdx.x * MT, cw = k * 4 + w, mt0 = k == 0 ? 0 : 2 * k + 1;
    uint32_t* x1s = reinterpret_cast<uint32_t*>(g_x1 + T0 * D_) + lane;
    WRing rg = make_ring(k, 0);
    mbar_wait(sb + M_BAR + MB_X * 8, 0, dl);
    {
        float acc[NT][56];
        mlp_gemm<NT, 112, false>(acc, sb, rg, 7, lane, dl);
        bar_sync(1, 384);
#pragma unroll 1
        for (int i = 0; i < NT; i++) {
            const int q = ((mt0 + i) * 64 + 16 * w) / 112;
            const int o0 = 8 * (lane >> 4) + (lane & 7) - (q == 0 ? 1 : q == 1 ? 3 : q == 2 ? 0 : 4);
            const uint32_t ad0 = sb + M_P + (mt0 + i) * PP + o0 * 128 + (((2 * w + ((lane >> 3) & 1)) ^ (o0 & 7)) << 4);
#pragma unroll 1
            for (int p = 0; p < 7; p++) {
                uint32_t r[4];
#pragma unroll
                for (int e = 0; e < 4; e++) {
                    r[e] = pack_bf(acc[0][2 * e], acc[0][2 * e + 1]);
                    r[e] = pack_bf(gelu_tanh(bf_lo(r[e])), gelu_tanh(bf_hi(r[e])));
                    if ((unsigned)(T0 - 2 + 2 * (lane & 3) + 16 * p + 8 * (e >> 1)) >= (unsigned)S_) r[e] = 0u;
                }
                stsm4t((unsigned)(o0 + 16 * p) < (unsigned)MT ? ad0 + p * 2048 : sb + M_STG + lane * 16, r[0], r[1], r[2], r[3]);
#pragma unroll
                for (int e = 0; e < 48; e++) acc[0][e] = acc[0][e + 8];
            }
            rotate_acc(acc);
        }
        fence_async_smem();
        bar_sync(1, 384);
    }
    {
        float acc[NT][52];
        mlp_gemm<NT, 104, false>(acc, sb, rg, 7, lane, dl);
        bar_sync(1, 384);
#pragma unroll 1
        for (int i = 0; i < NT; i++) { mlp_store<false>(acc[0], sb + M_P + (mt0 + i) * PP, w, lane); rotate_acc(acc); }
        mlp_rows(sb, x1s, cw, lane);
        fence_async_smem();
        bar_sync(1, 384);
    }
    {
        const uint32_t stg = sb + M_STG + k * 13312;
        const bool lead = w == 0 && lane == 0;
#pragma unroll 1
        for (int mt = k; mt < 28; mt += 3) {
            float acc[1][52];
            mlp_gemm<1, 104, false>(acc, sb, rg, 7, lane, dl);
            if (lead) asm volatile("cp.async.bulk.wait_group.read 0;" ::: "memory");
            bar_sync(2 + k, 128);
            mlp_store<true>(acc[0], stg, w, lane);
            fence_async_smem();
            bar_sync(2 + k, 128);
            if (lead) { tma_store(mH, mt * 64, T0, stg); asm volatile("cp.async.bulk.commit_group;" ::: "memory"); }
        }
        if (lead) {
            asm volatile("cp.async.bulk.wait_group 0;" ::: "memory");
            fence_async_all();
            mbar_arrive(sb + M_BAR + MB_RDY * 8);
        }
        __syncwarp();
    }
    {
        float acc[NT][52];
        mlp_gemm<NT, 104, true>(acc, sb, rg, 28, lane, dl);
        bar_sync(1, 384);
#pragma unroll 1
        for (int i = 0; i < NT; i++) { mlp_store<false>(acc[0], sb + M_P + (mt0 + i) * PP, w, lane); rotate_acc(acc); }
    }
    mlp_final(sb, x1s, x, out, cw, lane, stag, dl);
    bar_sync(1, 384);
    if (cw == 0 && lane == 0) {
        if (atomicInc(&g_done, NMLP - 1) == NMLP - 1) atomicAdd(&g_epoch, 1u);
    }
}

__global__ void __launch_bounds__(512, 1)
mlp_kernel(const __grid_constant__ CUtensorMap m1, const __grid_constant__ CUtensorMap m2, const __grid_constant__ CUtensorMap m3,
           const __grid_constant__ CUtensorMap m4, const __grid_constant__ CUtensorMap mH, const __grid_constant__ CUtensorMap mX, const bf16* __restrict__ x, bf16* __restrict__ out) {
    extern __shared__ unsigned char smem_raw[];
    const uint32_t sb = (smem_u32(smem_raw) + 1023u) & ~1023u;
    const uint32_t bars = sb + M_BAR;
    const uint32_t dl = clk() + DEADLINE;
    const int tid = threadIdx.x, lane = __shfl_sync(0xffffffffu, tid & 31, tid & 31);
    const int wg = __shfl_sync(0xffffffffu, tid >> 7, 0), w = __shfl_sync(0xffffffffu, (tid >> 5) & 3, 0);
    const uint32_t epoch = ldg_rlx32(&g_epoch), stag = (epoch & 1u) ^ 1u;
    if (lane == 0) {
        const int wi = tid >> 5;
        if (wi >= 10) {
            const CUtensorMap* m = wi == 10 ? &mX : wi == 11 ? &m1 : wi == 12 ? &m2 : wi == 13 ? &m3 : wi == 14 ? &m4 : &mH;
            asm volatile("prefetch.tensormap [%0];" :: "l"(m) : "memory");
        }
#pragma unroll 1
        for (int i = wi; i < MB_NUM; i += 16) mbar_init(bars + i * 8, i == MB_RDY ? 3 : i == MB_X ? 1 : i >= MB_HE ? 12 : (i >= MB_WE && i < MB_HF) ? 4 : 1);
        fence_async_smem();
    }
    __syncthreads();
    if (wg == 3) {
        asm volatile("setmaxnreg.dec.sync.aligned.u32 24;");
        if (lane == 0 && w < 3) {
            WRing rg = make_ring(w, 1);
            uint32_t tn = clk();
            const int nt = w == 0 ? 3 : 2, mt0 = w == 0 ? 0 : 2 * w + 1, n3 = w == 0 ? 70 : 63;
#pragma unroll 1
            for (int ph = 0; ph < 4; ph++) {
                const CUtensorMap* m = ph == 0 ? &m1 : ph == 1 ? &m2 : ph == 2 ? &m3 : &m4;
                const int cnt = ph == 2 ? n3 : (ph == 3 ? 28 : 7) * nt, inner = ph == 2 ? 7 : nt;
                int a = 0, b = 0;
                const uint32_t gap = ph == 2 ? PACE3 : ph == 3 ? PACE4 / nt : 0u;
#pragma unroll 1
                for (int n = 0; n < cnt; n++) {
                    const int cx = ph == 2 ? w + 3 * a : mt0 + b, cy = ph == 2 ? b : a;
                    spin_until(tn);
                    mbar_wait(bars + (MB_WE + rg.slot) * 8, rg.ph, dl);
                    mbar_expect(bars + (MB_WF + rg.slot) * 8, 8192);
                    tma_load_once(sb + M_W + rg.slot * 8192, m, cx * 64, cy * 64, bars + (MB_WF + rg.slot) * 8);
                    tn = clk() + gap;
                    rg.next();
                    if (++b == inner) { b = 0; a++; }
                }
            }
        } else if (lane == 0 && w == 3) {
            while ((int)(ldg_acq32(&g_start_cnt) - (epoch + 1) * NCHAIN) < 0) { if (expired(dl)) break; }
            fence_async_all();
            mbar_expect(bars + MB_X * 8, 7 * PP);
#pragma unroll 1
            for (int i = 0; i < 7; i++) tma_load(sb + M_P + i * PP, &mX, i * 64, blockIdx.x * MT - 2, bars + MB_X * 8);
            mbar_wait(bars + MB_RDY * 8, 0, dl);
            fence_async_all();
            uint32_t th = clk();
#pragma unroll 1
            for (int kb = 0; kb < 28; kb++) {
                const int hs = kb % 7;
                spin_until(th);
                mbar_wait(bars + (MB_HE + hs) * 8, ((kb / 7) & 1) ^ 1, dl);
                mbar_expect(bars + (MB_HF + hs) * 8, 13312);
                tma_load_once(sb + M_P + hs * PP, &mH, kb * 64, blockIdx.x * MT, bars + (MB_HF + hs) * 8);
                th = clk() + PACE4 - 100;
            }
        }
    } else if (wg == 0) {
        asm volatile("setmaxnreg.inc.sync.aligned.u32 200;");
        mlp_consumer<3>(&mH, x, out, sb, 0, w, lane, stag, dl);
    } else {
        asm volatile("setmaxnreg.inc.sync.aligned.u32 144;");
        mlp_consumer<2>(&mH, x, out, sb, wg, w, lane, stag, dl);
    }
}

__device__ bf16 f_h[S_ * D_];
__device__ bf16 f_g[S_ * D_];
__device__ bf16 f_mem[8 * D_];
__device__ float f_part[NH * 40 * D_];

__global__ void fb_ln(const bf16* __restrict__ in, bf16* __restrict__ o1, bf16* __restrict__ o2) {
    const int row = blockIdx.x * 8 + (threadIdx.x >> 5), lane = threadIdx.x & 31;
    uint32_t w[7];
    for (int i = 0; i < 7; i++) w[i] = reinterpret_cast<const uint32_t*>(in + row * D_)[lane + 32 * i];
    ln_row(w);
    for (int i = 0; i < 7; i++) reinterpret_cast<uint32_t*>(o1 + row * D_)[lane + 32 * i] = w[i];
    if (o2) {
        ln_row(w);
        for (int i = 0; i < 7; i++) reinterpret_cast<uint32_t*>(o2 + row * D_)[lane + 32 * i] = w[i];
    }
}
__global__ void fb_gemm(const bf16* __restrict__ A, const bf16* __restrict__ B, const bf16* __restrict__ res, bf16* __restrict__ C, int K, int N, int mode) {
    __shared__ float sa[16][65], sbm[16][65];
    const int tx = threadIdx.x & 15, ty = threadIdx.x >> 4, m0 = blockIdx.y * 64, n0 = blockIdx.x * 64;
    float acc[4][4] = {};
    for (int k0 = 0; k0 < K; k0 += 16) {
        for (int i = threadIdx.x; i < 1024; i += 256) {
            sa[i & 15][i >> 4] = __bfloat162float(A[(m0 + (i >> 4)) * K + k0 + (i & 15)]);
            sbm[i >> 6][i & 63] = __bfloat162float(B[(k0 + (i >> 6)) * N + n0 + (i & 63)]);
        }
        __syncthreads();
        for (int k = 0; k < 16; k++)
            for (int a = 0; a < 4; a++)
                for (int b = 0; b < 4; b++) acc[a][b] += sa[k][ty * 4 + a] * sbm[k][tx * 4 + b];
        __syncthreads();
    }
    for (int a = 0; a < 4; a++)
        for (int b = 0; b < 4; b++) {
            const int m = m0 + ty * 4 + a, n = n0 + tx * 4 + b;
            const float v = rbf(acc[a][b]);
            if (mode == 0) {
                const int q = n / 112, sh = q == 0 ? 1 : q == 1 ? -1 : q == 2 ? 2 : -2, mo = m + sh;
                if (mo >= 0 && mo < S_) C[mo * N + n] = __float2bfloat16_rn(gelu_tanh(v));
                const int src = m - sh;
                if (src < 0 || src >= S_) C[m * N + n] = __float2bfloat16_rn(0.f);
            } else if (mode == 1) C[m * N + n] = __float2bfloat16_rn(__bfloat162float(res[m * N + n]) + v);
            else if (mode == 2) C[m * N + n] = __float2bfloat16_rn(gelu_tanh(v));
            else { const float y = rbf(__bfloat162float(res[m * N + n]) + v); C[m * N + n] = __float2bfloat16_rn(y / (1.0f + __expf(-y))); }
        }
}
__global__ void fb_step1(const bf16* __restrict__ mem, const bf16* __restrict__ Wq, const bf16* __restrict__ Wk, const bf16* __restrict__ Wv,
                         const bf16* __restrict__ Wo, int s) {
    extern __shared__ float fs[];
    float* hz = fs; float* q = hz + 40 * D_; float* k = q + 40 * 257; float* v = k + 40 * 257; float* p = v + 40 * 257;
    const int h = blockIdx.x, e = threadIdx.x;
    for (int i = e; i < 40 * D_; i += 256) hz[i] = __bfloat162float(i < 8 * D_ ? mem[i] : g_xn[s * 32 * D_ + i - 8 * D_]);
    __syncthreads();
    for (int r0 = 0; r0 < 40; r0 += 8) {
        float aq[8] = {}, ak[8] = {}, av[8] = {};
        for (int d = 0; d < D_; d++) {
            const float wq = __bfloat162float(Wq[d * 4096 + h * 256 + e]), wk = __bfloat162float(Wk[d * 4096 + h * 256 + e]), wv = __bfloat162float(Wv[d * 4096 + h * 256 + e]);
            for (int r = 0; r < 8; r++) { const float z = hz[(r0 + r) * D_ + d]; aq[r] += z * wq; ak[r] += z * wk; av[r] += z * wv; }
        }
        for (int r = 0; r < 8; r++) { q[(r0 + r) * 257 + e] = rbf(aq[r]); k[(r0 + r) * 257 + e] = rbf(ak[r]); v[(r0 + r) * 257 + e] = rbf(av[r]); }
    }
    __syncthreads();
    for (int i = e; i < 1600; i += 256) {
        const int a = i / 40, b = i % 40;
        float acc = 0.f;
        for (int c = 0; c < 256; c++) acc += q[a * 257 + c] * k[b * 257 + c];
        p[i] = (a < 8 || a >= b) ? rbf(rbf(acc) * 0.0625f) : -1e9f;
    }
    __syncthreads();
    if (e < 40) {
        float mx = p[e * 40], z = 0.f;
        for (int b = 1; b < 40; b++) mx = fmaxf(mx, p[e * 40 + b]);
        for (int b = 0; b < 40; b++) { p[e * 40 + b] = __expf(p[e * 40 + b] - mx); z += p[e * 40 + b]; }
        for (int b = 0; b < 40; b++) p[e * 40 + b] = rbf(p[e * 40 + b] / z);
    }
    __syncthreads();
    for (int a = 0; a < 40; a++) { float acc = 0.f; for (int b = 0; b < 40; b++) acc += p[a * 40 + b] * v[b * 257 + e]; q[a * 257 + e] = rbf(acc); }
    __syncthreads();
    for (int c = e; c < D_; c += 256)
        for (int r0 = 0; r0 < 40; r0 += 8) {
            float acc[8] = {};
            for (int d = 0; d < 256; d++) { const float wo = __bfloat162float(Wo[(h * 256 + d) * D_ + c]); for (int r = 0; r < 8; r++) acc[r] += q[(r0 + r) * 257 + d] * wo; }
            for (int r = 0; r < 8; r++) f_part[(h * 40 + r0 + r) * D_ + c] = acc[r];
        }
}
__global__ void fb_step2(int s) {
    const int i = blockIdx.x * 256 + threadIdx.x;
    if (i >= 40 * D_) return;
    float acc = 0.f;
    for (int h = 0; h < NH; h++) acc += f_part[h * 40 * D_ + i];
    if (i < 8 * D_) f_mem[i] = __float2bfloat16_rn(acc); else reinterpret_cast<float*>(g_sw)[s * 32 * D_ + i - 8 * D_] = acc;
}
__global__ void fb_final(const bf16* __restrict__ x, bf16* __restrict__ out) {
    const int i = blockIdx.x * 256 + threadIdx.x;
    out[i] = __float2bfloat16_rn(__bfloat162float(x[i]) + rbf(rbf(reinterpret_cast<const float*>(g_sw)[i]) * __bfloat162float(f_g[i])));
}

typedef CUresult (*EncodeFn)(CUtensorMap*, CUtensorMapDataType, cuuint32_t, void*, const cuuint64_t*, const cuuint64_t*, const cuuint32_t*,
                             const cuuint32_t*, CUtensorMapInterleave, CUtensorMapSwizzle, CUtensorMapL2promotion, CUtensorMapFloatOOBfill);
static bool make_map(EncodeFn fn, CUtensorMap* m, const void* p, uint64_t cols, uint64_t rows, uint32_t bc, uint32_t br) {
    cuuint64_t dim[2] = {cols, rows}, str[1] = {cols * 2};
    cuuint32_t box[2] = {bc, br}, es[2] = {1, 1};
    return fn(m, CU_TENSOR_MAP_DATA_TYPE_BFLOAT16, 2, const_cast<void*>(p), dim, str, box, es, CU_TENSOR_MAP_INTERLEAVE_NONE,
              CU_TENSOR_MAP_SWIZZLE_128B, CU_TENSOR_MAP_L2_PROMOTION_L2_256B, CU_TENSOR_MAP_FLOAT_OOB_FILL_NONE) == CUDA_SUCCESS;
}
template<typename T> static T* sym(T& s) { void* p = nullptr; cudaGetSymbolAddress(&p, s); return reinterpret_cast<T*>(p); }

static void fb_mlp(const bf16* x, const bf16* w1, const bf16* w2, const bf16* w3, const bf16* w4, cudaStream_t st) {
    bf16 *xn = (bf16*)sym(g_xn), *xn2 = (bf16*)sym(g_xn2), *hh = (bf16*)sym(f_h), *x1 = (bf16*)sym(g_x1), *h3 = (bf16*)sym(g_h3), *gg = (bf16*)sym(f_g);
    fb_ln<<<S_ / 8, 256, 0, st>>>(x, xn, xn2);
    fb_gemm<<<dim3(7, 32), 256, 0, st>>>(xn2, w1, nullptr, hh, D_, D_, 0);
    fb_gemm<<<dim3(7, 32), 256, 0, st>>>(hh, w2, xn, x1, D_, D_, 1);
    fb_ln<<<S_ / 8, 256, 0, st>>>(x1, xn2, nullptr);
    fb_gemm<<<dim3(28, 32), 256, 0, st>>>(xn2, w3, nullptr, h3, D_, F_, 2);
    fb_gemm<<<dim3(7, 32), 256, 0, st>>>(h3, w4, x1, gg, F_, D_, 3);
}

extern "C" void kernel_launch(void* const* d_in, const int* in_sizes, int n_in, void* d_out, int out_size) {
    const bf16 *x = (const bf16*)d_in[0], *mem0 = (const bf16*)d_in[1], *Wq = (const bf16*)d_in[2], *Wk = (const bf16*)d_in[3],
               *Wv = (const bf16*)d_in[4], *Wo = (const bf16*)d_in[5], *w1 = (const bf16*)d_in[8], *w2 = (const bf16*)d_in[9],
               *w3 = (const bf16*)d_in[10], *w4 = (const bf16*)d_in[11];
    bf16* out = (bf16*)d_out;
    cudaStream_t st = cudaStreamPerThread;

    cudaLaunchConfig_t cfg = {};
    cudaLaunchAttribute at[1];
    cfg.gridDim = dim3(NCHAIN); cfg.blockDim = dim3(CH_THREADS); cfg.dynamicSmemBytes = CH_SMEM; cfg.stream = st;
    at[0].id = cudaLaunchAttributeClusterDimension; at[0].val.clusterDim.x = CSZ; at[0].val.clusterDim.y = 1; at[0].val.clusterDim.z = 1;
    cfg.attrs = at; cfg.numAttrs = 1;

    static int mode = -1;
    static EncodeFn enc = nullptr;
    if (mode < 0) {
        void* fn = nullptr;
        cudaDriverEntryPointQueryResult qr;
        cudaGetDriverEntryPoint("cuTensorMapEncodeTiled", &fn, cudaEnableDefault, &qr);
        enc = (EncodeFn)fn;
        cudaFuncSetAttribute(chain_kernel, cudaFuncAttributeMaxDynamicSharedMemorySize, CH_SMEM);
        cudaFuncSetAttribute(chain_kernel, cudaFuncAttributeNonPortableClusterSizeAllowed, 1);
        cudaFuncSetAttribute(mlp_kernel, cudaFuncAttributeMaxDynamicSharedMemorySize, ML_SMEM);
        cudaFuncSetAttribute(fb_step1, cudaFuncAttributeMaxDynamicSharedMemorySize, (40 * D_ + 3 * 40 * 257 + 1600) * 4);
        int nc = 0;
        const cudaError_t e = cudaOccupancyMaxActiveClusters(&nc, chain_kernel, &cfg);
        mode = (e == cudaSuccess && nc >= NCL && enc != nullptr) ? 1 : 0;
        (void)cudaGetLastError();
    }
    if (mode == 1) {
        CUtensorMap mWq, mWk, mWv, mWo, mXn;
        bool ok = make_map(enc, &mWq, Wq, 4096, D_, 64, 64) && make_map(enc, &mWk, Wk, 4096, D_, 64, 112) && make_map(enc, &mWv, Wv, 4096, D_, 64, 112) &&
                  make_map(enc, &mWo, Wo, D_, 4096, 64, 64) && make_map(enc, &mXn, sym(g_xn), D_, S_, 64, 32);
        CUtensorMap m1, m2, m3, m4, mH, mX;
        ok = ok && make_map(enc, &m1, w1, D_, D_, 64, 64) && make_map(enc, &m2, w2, D_, D_, 64, 64) && make_map(enc, &m3, w3, F_, D_, 64, 64) &&
             make_map(enc, &m4, w4, D_, F_, 64, 64) && make_map(enc, &mH, sym(g_h3), F_, NMLP * MT, 64, MT) &&
             make_map(enc, &mX, sym(g_xn2), D_, S_, 64, 112);
        if (ok) {
            unsigned char* comm = (unsigned char*)(((uintptr_t)sym(g_comm) + (2u << 20) - 1) & ~(uintptr_t)((2u << 20) - 1));
            cudaLaunchKernelEx(&cfg, chain_kernel, mWq, mWk, mWv, mWo, mXn, x, mem0, comm);
            cudaLaunchConfig_t c2 = {};
            cudaLaunchAttribute a2[1];
            c2.gridDim = dim3(NMLP); c2.blockDim = dim3(512); c2.dynamicSmemBytes = ML_SMEM; c2.stream = st;
            a2[0].id = cudaLaunchAttributeProgrammaticStreamSerialization; a2[0].val.programmaticStreamSerializationAllowed = 1;
            c2.attrs = a2; c2.numAttrs = 1;
            cudaLaunchKernelEx(&c2, mlp_kernel, m1, m2, m3, m4, mH, mX, x, out);
            return;
        }
    }
    fb_mlp(x, w1, w2, w3, w4, st);
    for (int s = 0; s < NSEG; s++) {
        fb_step1<<<NH, 256, (40 * D_ + 3 * 40 * 257 + 1600) * 4, st>>>(s == 0 ? mem0 : (const bf16*)sym(f_mem), Wq, Wk, Wv, Wo, s);
        fb_step2<<<(40 * D_ + 255) / 256, 256, 0, st>>>(s);
    }
    fb_final<<<S_ * D_ / 256, 256, 0, st>>>(x, out);
}
```
